```python
import torch

def _softmax(x, axis=-1):
    return torch.softmax(x, dim=axis)
def _gelu(x):
    return torch.nn.functional.gelu(x, approximate="tanh")
def _silu(x):
    return torch.nn.functional.silu(x)
def _sigmoid(x):
    return torch.sigmoid(x)
def _layernorm(x, axis=-1, eps=1e-5):
    m = x.mean(dim=axis, keepdim=True)
    v = x.var(dim=axis, keepdim=True, unbiased=False)
    return (x - m) / torch.sqrt(v + eps)
def _scatter_add(tgt, idx, src, axis=0):
    return tgt.clone().index_add_(axis, idx, src)
def _segment_sum(src, seg, n):
    out = torch.zeros((n,) + src.shape[1:], dtype=src.dtype)
    return out.index_add_(0, seg, src)
def _pad(x, pw):
    flat = tuple(v for pair in reversed(pw) for v in pair)
    return torch.nn.functional.pad(x, flat)

kernel_name = 'concat_heads__spectral_fnet__ssm_conv_h3__prompt'

def setup_inputs():

    _w = (lambda a: (lambda t: t.to(torch.bfloat16) if t.is_floating_point() else t)(torch.as_tensor(a)))
    def _A_setup():
        B, S, D = 1, 2048, 1024
        ns = torch.arange(S)[:, None] * torch.arange(S)[None, :]
        nd = torch.arange(D)[:, None] * torch.arange(D)[None, :]
        Ws_re = torch.cos(-2.0 * torch.pi * ns / S).to(float)
        Ws_im = torch.sin(-2.0 * torch.pi * ns / S).to(float)
        Wd_re = torch.cos(-2.0 * torch.pi * nd / D).to(float)
        Wd_im = torch.sin(-2.0 * torch.pi * nd / D).to(float)
        return {
            "x": _w((lambda *s: torch.randn(*s, dtype=torch.bfloat16) * 0.05)(B, S, D)),
            "dft_seq_re": _w(Ws_re),
            "dft_seq_im": _w(Ws_im),
            "dft_hid_re": _w(Wd_re),
            "dft_hid_im": _w(Wd_im),
        }
    _A_in = _A_setup()

    def _B_setup():
        B, S, D = 1, 2048, 1024
        ks = 4
        return {
            "q": _w((lambda *s: torch.randn(*s, dtype=torch.bfloat16) * 0.05)(B, S, D)),
            "k": _w((lambda *s: torch.randn(*s, dtype=torch.bfloat16) * 3.2)(B, S, D)),
            "v": _w((lambda *s: torch.randn(*s, dtype=torch.bfloat16) * 3.2)(B, S, D)),
            "shift_k": _w((lambda *s: torch.randn(*s, dtype=torch.bfloat16) * 3.2)(D, ks) * 0.5),
            "ssm_k": _w((lambda *s: torch.randn(*s, dtype=torch.bfloat16) * 3.2)(D, S) * (1.0 / S ** 0.5)),
            "ssm_D": _w((lambda *s: torch.randn(*s, dtype=torch.bfloat16) * 3.2)(D)),
        }
    _B_in = _B_setup()

    return {
        "A_x": _A_in["x"],
        "A_dft_seq_re": _A_in["dft_seq_re"],
        "A_dft_seq_im": _A_in["dft_seq_im"],
        "A_dft_hid_re": _A_in["dft_hid_re"],
        "A_dft_hid_im": _A_in["dft_hid_im"],
        "B_q": _B_in["q"],
        "B_k": _B_in["k"],
        "B_v": _B_in["v"],
        "B_shift_k": _B_in["shift_k"],
        "B_ssm_k": _B_in["ssm_k"],
        "B_ssm_D": _B_in["ssm_D"],
    }

def reference(A_x, A_dft_seq_re, A_dft_seq_im, A_dft_hid_re, A_dft_hid_im, B_q, B_k, B_v, B_shift_k, B_ssm_k, B_ssm_D):
    def _A_ref(x, dft_seq_re, dft_seq_im, dft_hid_re, dft_hid_im):
        a = torch.einsum("bsd,ed->bse", x, dft_hid_re)
        b = torch.einsum("bsd,ed->bse", x, dft_hid_im)
        y = torch.einsum("ts,bse->bte", dft_seq_re, a) - torch.einsum("ts,bse->bte", dft_seq_im, b)
        return y

    def _B_ref(q, k, v, shift_k, ssm_k, ssm_D):
        B, S, D = q.shape
        ks = shift_k.shape[-1]
        k_pad = _pad(k, ((0, 0), (ks - 1, 0), (0, 0)))
        k_shift = torch.zeros_like(k)
        for t in range(ks):
            k_shift = k_shift + k_pad[:, t:t + S, :] * shift_k[:, ks - 1 - t][None, None, :]
        kv = k_shift * v
        L = 2 * S
        kv_pad = _pad(kv, ((0, 0), (0, S), (0, 0)))
        kf_pad = _pad(ssm_k, ((0, 0), (0, S)))
        kv_f = (lambda x, axes=(-2,-1): torch.fft.rfft2(x.float(), dim=axes))(kv_pad[:, None, :, :], axes=(1, 2))
        kf_f = (lambda x, axes=(-2,-1): torch.fft.rfft2(x.float(), dim=axes))(kf_pad[:, None, :], axes=(1, 2))
        kf_f = (lambda x, *d: x.permute(*d))(kf_f, 1, 2, 0)
        y_f = kv_f * kf_f[None, :, :, :]
        y = (lambda x, s, axes=(-2,-1): torch.fft.irfft2(x, s=s, dim=axes).to(torch.bfloat16))(y_f, (1, L), axes=(1, 2))[:, 0, :S, :]
        y = y + kv * ssm_D[None, None, :]
        return q * y

    a = _A_ref(A_x, A_dft_seq_re, A_dft_seq_im, A_dft_hid_re, A_dft_hid_im)
    b = _B_ref(B_q, B_k, B_v, B_shift_k, B_ssm_k, B_ssm_D)
    return torch.concatenate([a, b], axis=-1)
```

```cpp
#include <cuda_runtime.h>
#include <cuda_bf16.h>
#include <cuda.h>
#include <stdint.h>

#define S_LEN 2048
#define D_DIM 1024

__device__ __nv_bfloat16 g_abT[2048 * 2048];
__device__ unsigned int g_ready[8];
__device__ unsigned int g_passed[8];

__device__ __forceinline__ uint32_t smem_u32(const void* p) {
    return (uint32_t)__cvta_generic_to_shared(p);
}
__device__ __forceinline__ void mbar_init(uint32_t bar, uint32_t count) {
    asm volatile("mbarrier.init.shared::cta.b64 [%0], %1;" ::"r"(bar), "r"(count));
}
__device__ __forceinline__ void mbar_expect_tx(uint32_t bar, uint32_t bytes) {
    asm volatile("mbarrier.arrive.expect_tx.shared::cta.b64 _, [%0], %1;" ::"r"(bar), "r"(bytes) : "memory");
}
__device__ __forceinline__ void mbar_arrive(uint32_t bar) {
    asm volatile("mbarrier.arrive.shared::cta.b64 _, [%0];" ::"r"(bar) : "memory");
}
__device__ __forceinline__ void mbar_wait(uint32_t bar, uint32_t parity) {
    asm volatile(
        "{\n"
        ".reg .pred p;\n"
        "LAB_WAIT:\n"
        "mbarrier.try_wait.parity.shared::cta.b64 p, [%0], %1;\n"
        "@p bra DONE;\n"
        "bra LAB_WAIT;\n"
        "DONE:\n"
        "}\n" ::"r"(bar), "r"(parity) : "memory");
}
__device__ __forceinline__ void tma_load_2d(uint32_t dst, const CUtensorMap* map, uint32_t bar, int c0, int c1) {
    asm volatile(
        "cp.async.bulk.tensor.2d.shared::cluster.global.mbarrier::complete_tx::bytes [%0], [%1, {%3, %4}], [%2];"
        ::"r"(dst), "l"((uint64_t)map), "r"(bar), "r"(c0), "r"(c1) : "memory");
}
__device__ __forceinline__ void wgmma_fence() { asm volatile("wgmma.fence.sync.aligned;" ::: "memory"); }
__device__ __forceinline__ void wgmma_commit() { asm volatile("wgmma.commit_group.sync.aligned;" ::: "memory"); }
template <int N>
__device__ __forceinline__ void wgmma_wait() { asm volatile("wgmma.wait_group.sync.aligned %0;" ::"n"(N) : "memory"); }

__device__ __forceinline__ uint64_t make_desc_sw128(uint32_t saddr) {
    uint64_t d = 0;
    d |= (uint64_t)((saddr & 0x3FFFF) >> 4);
    d |= (uint64_t)1 << 16;
    d |= (uint64_t)64 << 32;
    d |= (uint64_t)1 << 62;
    return d;
}

#define ACC8(a, i) "+f"(a[i]), "+f"(a[i + 1]), "+f"(a[i + 2]), "+f"(a[i + 3]), "+f"(a[i + 4]), "+f"(a[i + 5]), "+f"(a[i + 6]), "+f"(a[i + 7])

__device__ __forceinline__ void wgmma_m64n256k16(float (&d)[128], uint64_t da, uint64_t db, int scale_d) {
    asm volatile(
        "{\n"
        ".reg .pred p;\n"
        "setp.ne.b32 p, %130, 0;\n"
        "wgmma.mma_async.sync.aligned.m64n256k16.f32.bf16.bf16 "
        "{%0, %1, %2, %3, %4, %5, %6, %7, %8, %9, %10, %11, %12, %13, %14, %15, "
        "%16, %17, %18, %19, %20, %21, %22, %23, %24, %25, %26, %27, %28, %29, %30, %31, "
        "%32, %33, %34, %35, %36, %37, %38, %39, %40, %41, %42, %43, %44, %45, %46, %47, "
        "%48, %49, %50, %51, %52, %53, %54, %55, %56, %57, %58, %59, %60, %61, %62, %63, "
        "%64, %65, %66, %67, %68, %69, %70, %71, %72, %73, %74, %75, %76, %77, %78, %79, "
        "%80, %81, %82, %83, %84, %85, %86, %87, %88, %89, %90, %91, %92, %93, %94, %95, "
        "%96, %97, %98, %99, %100, %101, %102, %103, %104, %105, %106, %107, %108, %109, %110, %111, "
        "%112, %113, %114, %115, %116, %117, %118, %119, %120, %121, %122, %123, %124, %125, %126, %127}, "
        "%128, %129, p, 1, 1, 0, 0;\n"
        "}\n"
        : ACC8(d, 0), ACC8(d, 8), ACC8(d, 16), ACC8(d, 24), ACC8(d, 32), ACC8(d, 40), ACC8(d, 48), ACC8(d, 56),
          ACC8(d, 64), ACC8(d, 72), ACC8(d, 80), ACC8(d, 88), ACC8(d, 96), ACC8(d, 104), ACC8(d, 112), ACC8(d, 120)
        : "l"(da), "l"(db), "r"(scale_d));
}

__device__ __forceinline__ void mma_bf16_16816(float (&c)[4], uint32_t a0, uint32_t a1, uint32_t a2, uint32_t a3,
                                               uint32_t b0, uint32_t b1) {
    asm volatile(
        "mma.sync.aligned.m16n8k16.row.col.f32.bf16.bf16.f32 {%0,%1,%2,%3}, {%4,%5,%6,%7}, {%8,%9}, {%0,%1,%2,%3};"
        : "+f"(c[0]), "+f"(c[1]), "+f"(c[2]), "+f"(c[3])
        : "r"(a0), "r"(a1), "r"(a2), "r"(a3), "r"(b0), "r"(b1));
}

__device__ __forceinline__ uint32_t lds32(uint32_t addr) {
    uint32_t v;
    asm volatile("ld.shared.b32 %0, [%1];" : "=r"(v) : "r"(addr));
    return v;
}
__device__ __forceinline__ uint32_t pack_bf16(float lo, float hi) {
    __nv_bfloat162 t = __floats2bfloat162_rn(lo, hi);
    return *reinterpret_cast<uint32_t*>(&t);
}
__device__ __forceinline__ float bf_lo(uint32_t v) { return __uint_as_float(v << 16); }
__device__ __forceinline__ float bf_hi(uint32_t v) { return __uint_as_float(v & 0xffff0000u); }
__device__ __forceinline__ float rbf(float x) { return __bfloat162float(__float2bfloat16_rn(x)); }

__device__ __forceinline__ void named_bar_sync(int id, int n) {
    asm volatile("bar.sync %0, %1;" ::"r"(id), "r"(n) : "memory");
}

constexpr int BM = 128, BN = 256, BK = 64, STAGES = 4;
constexpr int A_BYTES = BM * BK * 2;
constexpr int B_BYTES = BN * BK * 2;
constexpr int STAGE_BYTES = A_BYTES + B_BYTES;
constexpr int SMEM_BYTES = STAGES * STAGE_BYTES + 1024;
constexpr int NTHREADS = 384;

constexpr int STG_PITCH = 528;
constexpr int STG_WG_BYTES = 64 * STG_PITCH;

constexpr int KV_PITCH = 128 + 2048 + 8;
constexpr int KV_BYTES = 8 * KV_PITCH * 2;
constexpr int REV_PITCH = 2048 + 32 + 8;
constexpr int REV_BYTES = 8 * 2 * REV_PITCH * 2;
constexpr int YS_BYTES = 2048 * 8 * 2;
constexpr int CONV_KV_OFF = 0;
constexpr int CONV_REV_OFF = CONV_KV_OFF + KV_BYTES;
constexpr int CONV_YS_OFF = CONV_REV_OFF + REV_BYTES;
static_assert(CONV_YS_OFF + YS_BYTES <= STAGES * STAGE_BYTES, "conv smem");
constexpr int REV_Y0 = 2048;

struct Params {
    const __nv_bfloat16 *q, *k, *v, *shift_k, *ssm_k, *ssm_D;
    __nv_bfloat16* out;
};

struct PipeState {
    int stage;
    uint32_t phase;
    __device__ __forceinline__ void advance() {
        if (++stage == STAGES) { stage = 0; phase ^= 1; }
    }
};

__device__ __forceinline__ void gemm_produce(PipeState& ps, uint32_t sbase, uint32_t full0, uint32_t empty0,
                                             const CUtensorMap* mA, const CUtensorMap* mB, int arow, int brow, int nk) {
    for (int it = 0; it < nk; ++it) {
        mbar_wait(empty0 + 8 * ps.stage, ps.phase ^ 1);
        uint32_t fb = full0 + 8 * ps.stage;
        mbar_expect_tx(fb, STAGE_BYTES);
        uint32_t sa = sbase + ps.stage * STAGE_BYTES;
        tma_load_2d(sa, mA, fb, it * BK, arow);
        tma_load_2d(sa + A_BYTES, mB, fb, it * BK, brow);
        ps.advance();
    }
}

__device__ __forceinline__ void gemm_consume(PipeState& ps, float (&acc)[128], uint32_t sbase, uint32_t full0,
                                             uint32_t empty0, int wg, int nk) {
    int prev_stage = -1;
    for (int it = 0; it < nk; ++it) {
        mbar_wait(full0 + 8 * ps.stage, ps.phase);
        uint32_t sa = sbase + ps.stage * STAGE_BYTES + wg * (64 * 128);
        uint32_t sb = sbase + ps.stage * STAGE_BYTES + A_BYTES;
        uint64_t da = make_desc_sw128(sa);
        uint64_t db = make_desc_sw128(sb);
        wgmma_fence();
#pragma unroll
        for (int kk = 0; kk < 4; ++kk) {
            wgmma_m64n256k16(acc, da + (uint64_t)(kk * 2), db + (uint64_t)(kk * 2), (it > 0 || kk > 0) ? 1 : 0);
        }
        wgmma_commit();
        if (prev_stage >= 0) {
            wgmma_wait<1>();
            if ((threadIdx.x & 31) == 0) mbar_arrive(empty0 + 8 * prev_stage);
        }
        prev_stage = ps.stage;
        ps.advance();
    }
    wgmma_wait<0>();
    if ((threadIdx.x & 31) == 0) mbar_arrive(empty0 + 8 * prev_stage);
}

__device__ __forceinline__ void store_tile_bf16(const uint32_t (&pk)[64], uint8_t* stg, __nv_bfloat16* gdst, int ld,
                                                int wg_tid, int bar_id) {
    const int warp = wg_tid >> 5, lane = wg_tid & 31;
    const int r0 = warp * 16 + (lane >> 2);
    const int c0 = (lane & 3) * 2;
#pragma unroll
    for (int j = 0; j < 32; ++j) {
        *reinterpret_cast<uint32_t*>(stg + r0 * STG_PITCH + (j * 8 + c0) * 2) = pk[2 * j];
        *reinterpret_cast<uint32_t*>(stg + (r0 + 8) * STG_PITCH + (j * 8 + c0) * 2) = pk[2 * j + 1];
    }
    named_bar_sync(bar_id, 128);
#pragma unroll
    for (int p = 0; p < 16; ++p) {
        int r = p * 4 + (wg_tid >> 5);
        int cb = (wg_tid & 31) * 16;
        uint4 val = *reinterpret_cast<const uint4*>(stg + r * STG_PITCH + cb);
        *reinterpret_cast<uint4*>(reinterpret_cast<uint8_t*>(gdst + (size_t)r * ld) + cb) = val;
    }
}

__device__ __forceinline__ void conv_phase(const Params& p, uint8_t* smem, int ch0, int ctid) {
    const int warp = ctid >> 5, lane = ctid & 31;
    __nv_bfloat16* kvs = reinterpret_cast<__nv_bfloat16*>(smem + CONV_KV_OFF);
    __nv_bfloat16* rev = reinterpret_cast<__nv_bfloat16*>(smem + CONV_REV_OFF);
    __nv_bfloat16* ys = reinterpret_cast<__nv_bfloat16*>(smem + CONV_YS_OFF);

    float sk[8][4];
#pragma unroll
    for (int c = 0; c < 8; ++c) {
        uint2 t = *reinterpret_cast<const uint2*>(p.shift_k + (size_t)(ch0 + c) * 4);
        sk[c][0] = bf_lo(t.x); sk[c][1] = bf_hi(t.x); sk[c][2] = bf_lo(t.y); sk[c][3] = bf_hi(t.y);
    }
#pragma unroll 2
    for (int it = 0; it < 8; ++it) {
        int s = ctid + 256 * it;
        uint4 kr[4];
#pragma unroll
        for (int j = 0; j < 4; ++j) {
            int sj = s - j;
            if (sj >= 0) kr[j] = *reinterpret_cast<const uint4*>(p.k + (size_t)sj * D_DIM + ch0);
            else kr[j] = make_uint4(0, 0, 0, 0);
        }
        uint4 vr = *reinterpret_cast<const uint4*>(p.v + (size_t)s * D_DIM + ch0);
        const uint32_t* vv = reinterpret_cast<const uint32_t*>(&vr);
#pragma unroll
        for (int c = 0; c < 8; ++c) {
            float kk[4];
#pragma unroll
            for (int j = 0; j < 4; ++j) {
                uint32_t w = reinterpret_cast<const uint32_t*>(&kr[j])[c >> 1];
                kk[j] = (c & 1) ? bf_hi(w) : bf_lo(w);
            }
            float a = rbf(kk[3] * sk[c][3]);
            a = rbf(a + rbf(kk[2] * sk[c][2]));
            a = rbf(a + rbf(kk[1] * sk[c][1]));
            a = rbf(a + rbf(kk[0] * sk[c][0]));
            float vf = (c & 1) ? bf_hi(vv[c >> 1]) : bf_lo(vv[c >> 1]);
            kvs[c * KV_PITCH + 128 + s] = __float2bfloat16_rn(a * vf);
        }
    }
    if (ctid < 8 * 16) {
        int c = ctid >> 4, i = ctid & 15;
        *reinterpret_cast<uint4*>(kvs + c * KV_PITCH + i * 8) = make_uint4(0, 0, 0, 0);
    }
    {
        __nv_bfloat16* r0 = rev + (size_t)(warp * 2) * REV_PITCH;
        __nv_bfloat16* r1 = r0 + REV_PITCH;
        const __nv_bfloat16* h = p.ssm_k + (size_t)(ch0 + warp) * S_LEN;
#pragma unroll
        for (int it = 0; it < 8; ++it) {
            int idx = 8 * (lane + 32 * it);
            uint4 hv = *reinterpret_cast<const uint4*>(h + idx);
            const __nv_bfloat16* he = reinterpret_cast<const __nv_bfloat16*>(&hv);
#pragma unroll
            for (int e = 0; e < 8; ++e) {
                r0[REV_Y0 - (idx + e)] = he[e];
                r1[REV_Y0 + 1 - (idx + e)] = he[e];
            }
        }
        if (lane < 24) {
            int idx = -1 - lane;
            r0[REV_Y0 - idx] = __float2bfloat16_rn(0.f);
            r1[REV_Y0 + 1 - idx] = __float2bfloat16_rn(0.f);
        }
    }
    named_bar_sync(1, 256);

    float acc[16][4];
#pragma unroll
    for (int i = 0; i < 16; ++i) { acc[i][0] = acc[i][1] = acc[i][2] = acc[i][3] = 0.f; }
    const int g = lane >> 2, c2 = (lane & 3) * 2;
    const uint32_t rev_base = smem_u32(rev + (size_t)(warp * 2 + (g & 1)) * REV_PITCH) +
                              2u * (uint32_t)(REV_Y0 + (g & 1) - g + c2);
    const uint32_t kv_base = smem_u32(kvs + (size_t)warp * KV_PITCH + 128) + 2u * (uint32_t)(16 * g + c2);
#pragma unroll 1
    for (int a = 0; a < 8; ++a) {
        uint32_t f[16][3];
#pragma unroll
        for (int q = 0; q < 16; ++q) {
            int delta = 16 * a + 128 * q;
            f[q][0] = lds32(rev_base - 2u * (uint32_t)(delta - 8));
            f[q][1] = lds32(rev_base - 2u * (uint32_t)(delta));
            f[q][2] = lds32(rev_base - 2u * (uint32_t)(delta + 8));
        }
        const uint32_t kva = kv_base - 32u * (uint32_t)a;
#pragma unroll
        for (int G = 0; G < 16; ++G) {
            uint32_t b0 = lds32(kva + 256u * G);
            uint32_t b1 = lds32(kva + 256u * G + 16u);
#pragma unroll
            for (int q = 0; q < 16 - G; ++q) {
                mma_bf16_16816(acc[G + q], f[q][1], f[q][2], f[q][0], f[q][1], b0, b1);
            }
        }
    }
    {
        const float Dv = __bfloat162float(p.ssm_D[ch0 + warp]);
        const __nv_bfloat16* kvc = kvs + (size_t)warp * KV_PITCH + 128;
#pragma unroll
        for (int I = 0; I < 16; ++I) {
#pragma unroll
            for (int e = 0; e < 4; ++e) {
                int s = 16 * (8 * I + c2 + (e & 1)) + g + 8 * (e >> 1);
                float kvv = __bfloat162float(kvc[s]);
                float y = rbf(acc[I][e]) + rbf(kvv * Dv);
                ys[s * 8 + warp] = __float2bfloat16_rn(y);
            }
        }
    }
    named_bar_sync(1, 256);
#pragma unroll 2
    for (int it = 0; it < 8; ++it) {
        int s = ctid + 256 * it;
        uint4 qv = *reinterpret_cast<const uint4*>(p.q + (size_t)s * D_DIM + ch0);
        uint4 yv = *reinterpret_cast<const uint4*>(ys + s * 8);
        uint4 ov;
        const uint32_t* qq = reinterpret_cast<const uint32_t*>(&qv);
        const uint32_t* yy = reinterpret_cast<const uint32_t*>(&yv);
        uint32_t* oo = reinterpret_cast<uint32_t*>(&ov);
#pragma unroll
        for (int e = 0; e < 4; ++e) oo[e] = pack_bf16(bf_lo(qq[e]) * bf_lo(yy[e]), bf_hi(qq[e]) * bf_hi(yy[e]));
        *reinterpret_cast<uint4*>(p.out + (size_t)s * 2048 + 1024 + ch0) = ov;
    }
}

__global__ void __cluster_dims__(2, 1, 1) __launch_bounds__(NTHREADS, 1)
fused_kernel(const __grid_constant__ CUtensorMap mWre, const __grid_constant__ CUtensorMap mWim,
             const __grid_constant__ CUtensorMap mX, const __grid_constant__ CUtensorMap mAB,
             const __grid_constant__ CUtensorMap mCr, const __grid_constant__ CUtensorMap mCi,
             const Params p) {
    extern __shared__ uint8_t smem_raw[];
    __shared__ __align__(8) uint64_t bars[2 * STAGES];
    uint8_t* smem = reinterpret_cast<uint8_t*>((reinterpret_cast<uintptr_t>(smem_raw) + 1023) & ~(uintptr_t)1023);
    const uint32_t sbase = smem_u32(smem);
    const uint32_t full0 = smem_u32(&bars[0]);
    const uint32_t empty0 = smem_u32(&bars[STAGES]);
    const int tid = threadIdx.x;
    const int wgid = tid >> 7;
    const int bid = blockIdx.x;

    if (tid == 0) {
        for (int i = 0; i < STAGES; ++i) {
            mbar_init(full0 + 8 * i, 1);
            mbar_init(empty0 + 8 * i, 8);
        }
        asm volatile("fence.mbarrier_init.release.cluster;" ::: "memory");
    }
    __syncthreads();

    const int g1_m = bid >> 3, g1_n = bid & 7;
    const int pair = bid >> 1, part = bid & 1;
    const int g2_m = pair >> 2, g2_n = pair & 3;
    const int grp = part * 4 + g2_n;

    if (wgid == 0) {
        asm volatile("setmaxnreg.dec.sync.aligned.u32 40;");
        if (tid == 0) {
            PipeState ps{0, 0};
            const CUtensorMap* mW = (g1_m < 8) ? &mWre : &mWim;
            gemm_produce(ps, sbase, full0, empty0, mW, &mX, (g1_m & 7) * BM, g1_n * BN, D_DIM / BK);
        }
        __syncwarp();
        named_bar_sync(2, NTHREADS);
        if (tid == 0) {
            unsigned int v;
            long long spins = 0;
            do {
                asm volatile("ld.acquire.gpu.global.u32 %0, [%1];" : "=r"(v) : "l"(&g_ready[grp]) : "memory");
            } while (v < 16u && ++spins < (1ll << 26));
            asm volatile("fence.proxy.async;" ::: "memory");
            unsigned int old = atomicAdd(&g_passed[grp], 1u);
            if (old == 15u) {
                g_passed[grp] = 0;
                g_ready[grp] = 0;
                __threadfence();
            }
            PipeState ps{0, 0};
            const CUtensorMap* mC = part ? &mCi : &mCr;
            gemm_produce(ps, sbase, full0, empty0, mC, &mAB, g2_m * BM, grp * BN, S_LEN / BK);
        }
        __syncwarp();
        asm volatile("barrier.cluster.arrive.release.aligned;\n barrier.cluster.wait.acquire.aligned;" ::: "memory");
        asm volatile("barrier.cluster.arrive.release.aligned;\n barrier.cluster.wait.acquire.aligned;" ::: "memory");
    } else {
        asm volatile("setmaxnreg.inc.sync.aligned.u32 232;");
        const int wg = wgid - 1;
        const int ctid = tid - 128;
        const int wtid = tid & 127;
        PipeState ps{0, 0};
        float acc[128];
        gemm_consume(ps, acc, sbase, full0, empty0, wg, D_DIM / BK);
        named_bar_sync(1, 256);
        {
            uint32_t pk[64];
#pragma unroll
            for (int i = 0; i < 64; ++i) pk[i] = pack_bf16(acc[2 * i], acc[2 * i + 1]);
            __nv_bfloat16* dst = g_abT + (size_t)(g1_m * BM + wg * 64) * 2048 + g1_n * BN;
            store_tile_bf16(pk, smem + wg * STG_WG_BYTES, dst, 2048, wtid, 3 + wg);
        }
        __threadfence();
        asm volatile("fence.proxy.async;" ::: "memory");
        named_bar_sync(1, 256);
        if (ctid == 0) {
            asm volatile("red.release.gpu.global.add.u32 [%0], 1;" ::"l"(&g_ready[g1_m >> 1]) : "memory");
        }
        conv_phase(p, smem, bid * 8, ctid);
        asm volatile("fence.proxy.async;" ::: "memory");
        named_bar_sync(2, NTHREADS);
        gemm_consume(ps, acc, sbase, full0, empty0, wg, S_LEN / BK);
        named_bar_sync(1, 256);
        asm volatile("barrier.cluster.arrive.release.aligned;\n barrier.cluster.wait.acquire.aligned;" ::: "memory");
        uint32_t pk[64];
#pragma unroll
        for (int i = 0; i < 64; ++i) pk[i] = pack_bf16(acc[2 * i], acc[2 * i + 1]);
        const uint32_t xbuf = sbase + 2 * STG_WG_BYTES + 1024;
        const bool sender = (wg != part);
        if (sender) {
            uint32_t remote;
            asm volatile("mapa.shared::cluster.u32 %0, %1, %2;" : "=r"(remote) : "r"(xbuf), "r"(part ^ 1));
#pragma unroll
            for (int i = 0; i < 64; ++i) {
                asm volatile("st.shared::cluster.b32 [%0], %1;" ::"r"(remote + (uint32_t)(i * 512 + wtid * 4)), "r"(pk[i]) : "memory");
            }
        }
        asm volatile("barrier.cluster.arrive.release.aligned;\n barrier.cluster.wait.acquire.aligned;" ::: "memory");
        if (!sender) {
#pragma unroll
            for (int i = 0; i < 64; ++i) {
                uint32_t o = lds32(xbuf + (uint32_t)(i * 512 + wtid * 4));
                uint32_t re = part ? o : pk[i];
                uint32_t im = part ? pk[i] : o;
                pk[i] = pack_bf16(bf_lo(re) - bf_lo(im), bf_hi(re) - bf_hi(im));
            }
            __nv_bfloat16* dst = p.out + (size_t)(g2_m * BM + wg * 64) * 2048 + g2_n * BN;
            store_tile_bf16(pk, smem + wg * STG_WG_BYTES, dst, 2048, wtid, 3 + wg);
        }
    }
}

typedef CUresult (*PFN_encodeTiled)(CUtensorMap*, CUtensorMapDataType, cuuint32_t, void*, const cuuint64_t*,
                                    const cuuint64_t*, const cuuint32_t*, const cuuint32_t*, CUtensorMapInterleave,
                                    CUtensorMapSwizzle, CUtensorMapL2promotion, CUtensorMapFloatOOBfill);

static void make_map(PFN_encodeTiled enc, CUtensorMap* m, const void* ptr, int rows, int cols, int box_rows) {
    cuuint64_t gdim[2] = {(cuuint64_t)cols, (cuuint64_t)rows};
    cuuint64_t gstr[1] = {(cuuint64_t)cols * 2};
    cuuint32_t box[2] = {64, (cuuint32_t)box_rows};
    cuuint32_t estr[2] = {1, 1};
    enc(m, CU_TENSOR_MAP_DATA_TYPE_BFLOAT16, 2, const_cast<void*>(ptr), gdim, gstr, box, estr,
        CU_TENSOR_MAP_INTERLEAVE_NONE, CU_TENSOR_MAP_SWIZZLE_128B, CU_TENSOR_MAP_L2_PROMOTION_L2_256B,
        CU_TENSOR_MAP_FLOAT_OOB_FILL_NONE);
}

extern "C" void kernel_launch(void* const* d_in, const int* in_sizes, int n_in, void* d_out, int out_size) {
    static PFN_encodeTiled enc = nullptr;
    static bool attr_set = false;
    if (!enc) {
        void* fn = nullptr;
        cudaDriverEntryPointQueryResult qres;
        cudaGetDriverEntryPoint("cuTensorMapEncodeTiled", &fn, cudaEnableDefault, &qres);
        enc = (PFN_encodeTiled)fn;
    }
    if (!attr_set) {
        cudaFuncSetAttribute(fused_kernel, cudaFuncAttributeMaxDynamicSharedMemorySize, SMEM_BYTES);
        attr_set = true;
    }
    void* abT = nullptr;
    cudaGetSymbolAddress(&abT, g_abT);

    CUtensorMap mWre, mWim, mX, mAB, mCr, mCi;
    make_map(enc, &mX, d_in[0], 2048, 1024, BN);
    make_map(enc, &mCr, d_in[1], 2048, 2048, BM);
    make_map(enc, &mCi, d_in[2], 2048, 2048, BM);
    make_map(enc, &mWre, d_in[3], 1024, 1024, BM);
    make_map(enc, &mWim, d_in[4], 1024, 1024, BM);
    make_map(enc, &mAB, abT, 2048, 2048, BN);

    Params p;
    p.q = (const __nv_bfloat16*)d_in[5];
    p.k = (const __nv_bfloat16*)d_in[6];
    p.v = (const __nv_bfloat16*)d_in[7];
    p.shift_k = (const __nv_bfloat16*)d_in[8];
    p.ssm_k = (const __nv_bfloat16*)d_in[9];
    p.ssm_D = (const __nv_bfloat16*)d_in[10];
    p.out = (__nv_bfloat16*)d_out;

    fused_kernel<<<128, NTHREADS, SMEM_BYTES>>>(mWre, mWim, mX, mAB, mCr, mCi, p);
}
```

```cpp
#include <cuda_runtime.h>
#include <cuda_bf16.h>
#include <cuda.h>
#include <stdint.h>

#define S_LEN 2048
#define D_DIM 1024

__device__ __nv_bfloat16 g_abT[2048 * 2048];
__device__ unsigned int g_ready[8];
__device__ unsigned int g_passed[8];
__device__ __nv_bfloat16 g_kvT[1024 * 2048];
__device__ __nv_bfloat16 g_yT[1024 * 2048];
__device__ unsigned int g_sync[4];
#define TSTAMP(i)
#define TSTAMP2(i)

__device__ __forceinline__ uint32_t smem_u32(const void* p) {
    return (uint32_t)__cvta_generic_to_shared(p);
}
__device__ __forceinline__ void mbar_init(uint32_t bar, uint32_t count) {
    asm volatile("mbarrier.init.shared::cta.b64 [%0], %1;" ::"r"(bar), "r"(count));
}
__device__ __forceinline__ void mbar_expect_tx(uint32_t bar, uint32_t bytes) {
    asm volatile("mbarrier.arrive.expect_tx.shared::cta.b64 _, [%0], %1;" ::"r"(bar), "r"(bytes) : "memory");
}
__device__ __forceinline__ void mbar_arrive(uint32_t bar) {
    asm volatile("mbarrier.arrive.shared::cta.b64 _, [%0];" ::"r"(bar) : "memory");
}
__device__ __forceinline__ void mbar_wait(uint32_t bar, uint32_t parity) {
    asm volatile(
        "{\n"
        ".reg .pred p;\n"
        "LAB_WAIT:\n"
        "mbarrier.try_wait.parity.shared::cta.b64 p, [%0], %1;\n"
        "@p bra DONE;\n"
        "bra LAB_WAIT;\n"
        "DONE:\n"
        "}\n" ::"r"(bar), "r"(parity) : "memory");
}
__device__ __forceinline__ void tma_load_2d(uint32_t dst, const CUtensorMap* map, uint32_t bar, int c0, int c1) {
    asm volatile(
        "cp.async.bulk.tensor.2d.shared::cluster.global.mbarrier::complete_tx::bytes [%0], [%1, {%3, %4}], [%2];"
        ::"r"(dst), "l"((uint64_t)map), "r"(bar), "r"(c0), "r"(c1) : "memory");
}
__device__ __forceinline__ void wgmma_fence() { asm volatile("wgmma.fence.sync.aligned;" ::: "memory"); }
__device__ __forceinline__ void wgmma_commit() { asm volatile("wgmma.commit_group.sync.aligned;" ::: "memory"); }
template <int N>
__device__ __forceinline__ void wgmma_wait() { asm volatile("wgmma.wait_group.sync.aligned %0;" ::"n"(N) : "memory"); }

__device__ __forceinline__ uint64_t make_desc_sw128(uint32_t saddr) {
    uint64_t d = 0;
    d |= (uint64_t)((saddr & 0x3FFFF) >> 4);
    d |= (uint64_t)1 << 16;
    d |= (uint64_t)64 << 32;
    d |= (uint64_t)1 << 62;
    return d;
}

#define ACC8(a, i) "+f"(a[i]), "+f"(a[i + 1]), "+f"(a[i + 2]), "+f"(a[i + 3]), "+f"(a[i + 4]), "+f"(a[i + 5]), "+f"(a[i + 6]), "+f"(a[i + 7])

__device__ __forceinline__ void wgmma_m64n256k16(float (&d)[128], uint64_t da, uint64_t db, int scale_d) {
    asm volatile(
        "{\n"
        ".reg .pred p;\n"
        "setp.ne.b32 p, %130, 0;\n"
        "wgmma.mma_async.sync.aligned.m64n256k16.f32.bf16.bf16 "
        "{%0, %1, %2, %3, %4, %5, %6, %7, %8, %9, %10, %11, %12, %13, %14, %15, "
        "%16, %17, %18, %19, %20, %21, %22, %23, %24, %25, %26, %27, %28, %29, %30, %31, "
        "%32, %33, %34, %35, %36, %37, %38, %39, %40, %41, %42, %43, %44, %45, %46, %47, "
        "%48, %49, %50, %51, %52, %53, %54, %55, %56, %57, %58, %59, %60, %61, %62, %63, "
        "%64, %65, %66, %67, %68, %69, %70, %71, %72, %73, %74, %75, %76, %77, %78, %79, "
        "%80, %81, %82, %83, %84, %85, %86, %87, %88, %89, %90, %91, %92, %93, %94, %95, "
        "%96, %97, %98, %99, %100, %101, %102, %103, %104, %105, %106, %107, %108, %109, %110, %111, "
        "%112, %113, %114, %115, %116, %117, %118, %119, %120, %121, %122, %123, %124, %125, %126, %127}, "
        "%128, %129, p, 1, 1, 0, 0;\n"
        "}\n"
        : ACC8(d, 0), ACC8(d, 8), ACC8(d, 16), ACC8(d, 24), ACC8(d, 32), ACC8(d, 40), ACC8(d, 48), ACC8(d, 56),
          ACC8(d, 64), ACC8(d, 72), ACC8(d, 80), ACC8(d, 88), ACC8(d, 96), ACC8(d, 104), ACC8(d, 112), ACC8(d, 120)
        : "l"(da), "l"(db), "r"(scale_d));
}

__device__ __forceinline__ void mma_bf16_16816(float (&c)[4], uint32_t a0, uint32_t a1, uint32_t a2, uint32_t a3,
                                               uint32_t b0, uint32_t b1) {
    asm volatile(
        "mma.sync.aligned.m16n8k16.row.col.f32.bf16.bf16.f32 {%0,%1,%2,%3}, {%4,%5,%6,%7}, {%8,%9}, {%0,%1,%2,%3};"
        : "+f"(c[0]), "+f"(c[1]), "+f"(c[2]), "+f"(c[3])
        : "r"(a0), "r"(a1), "r"(a2), "r"(a3), "r"(b0), "r"(b1));
}

__device__ __forceinline__ uint32_t lds32(uint32_t addr) {
    uint32_t v;
    asm volatile("ld.shared.b32 %0, [%1];" : "=r"(v) : "r"(addr));
    return v;
}
__device__ __forceinline__ uint32_t pack_bf16(float lo, float hi) {
    __nv_bfloat162 t = __floats2bfloat162_rn(lo, hi);
    return *reinterpret_cast<uint32_t*>(&t);
}
__device__ __forceinline__ float bf_lo(uint32_t v) { return __uint_as_float(v << 16); }
__device__ __forceinline__ float bf_hi(uint32_t v) { return __uint_as_float(v & 0xffff0000u); }
__device__ __forceinline__ __nv_bfloat162 u2b(uint32_t v) { return *reinterpret_cast<__nv_bfloat162*>(&v); }
__device__ __forceinline__ uint32_t b2u(__nv_bfloat162 v) { return *reinterpret_cast<uint32_t*>(&v); }
__device__ __forceinline__ float rbf(float x) { return __bfloat162float(__float2bfloat16_rn(x)); }

__device__ __forceinline__ void named_bar_sync(int id, int n) {
    asm volatile("bar.sync %0, %1;" ::"r"(id), "r"(n) : "memory");
}

constexpr int BM = 128, BN = 256, BK = 64, STAGES = 4;
constexpr int A_BYTES = BM * BK * 2;
constexpr int B_BYTES = BN * BK * 2;
constexpr int STAGE_BYTES = A_BYTES + B_BYTES;
constexpr int SMEM_BYTES = STAGES * STAGE_BYTES + 34688 + 1024;
constexpr int NTHREADS = 384;

constexpr int STG_PITCH = 528;
constexpr int STG_WG_BYTES = 64 * STG_PITCH;

constexpr int KV_PITCH = 112 + 2048 + 8;
constexpr int KV_BYTES = 8 * KV_PITCH * 2;
constexpr int REV_PITCH = 2048 + 32 + 8;
constexpr int REV_BYTES = 8 * 2 * REV_PITCH * 2;
constexpr int YS_BYTES = 2048 * 8 * 2;
constexpr int CONV_KV_OFF = STAGES * STAGE_BYTES;
constexpr int CONV_REV_OFF = 2 * STAGE_BYTES;
constexpr int STG1_OFF = 2 * STAGE_BYTES;
constexpr int CONV_YS_OFF = CONV_REV_OFF + REV_BYTES;
static_assert(CONV_REV_OFF + REV_BYTES <= STAGES * STAGE_BYTES && STG1_OFF + 2 * STG_WG_BYTES <= STAGES * STAGE_BYTES && KV_BYTES <= 34688, "conv smem");
constexpr int REV_Y0 = 2048;

struct Params {
    const __nv_bfloat16 *q, *k, *v, *shift_k, *ssm_k, *ssm_D;
    __nv_bfloat16* out;
};

struct PipeState {
    int stage;
    uint32_t phase;
    __device__ __forceinline__ void advance() {
        if (++stage == STAGES) { stage = 0; phase ^= 1; }
    }
};

__device__ __forceinline__ void gemm_produce(PipeState& ps, uint32_t sbase, uint32_t full0, uint32_t empty0,
                                             const CUtensorMap* mA, const CUtensorMap* mB, int arow, int brow, int k0, int nk) {
#pragma unroll 1
    for (int it = k0; it < nk; ++it) {
        mbar_wait(empty0 + 8 * ps.stage, ps.phase ^ 1);
        uint32_t fb = full0 + 8 * ps.stage;
        mbar_expect_tx(fb, STAGE_BYTES);
        uint32_t sa = sbase + ps.stage * STAGE_BYTES;
        tma_load_2d(sa, mA, fb, it * BK, arow);
        tma_load_2d(sa + A_BYTES, mB, fb, it * BK, brow);
        ps.advance();
    }
}

__device__ __forceinline__ void gemm_consume(PipeState& ps, float (&acc)[128], uint32_t sbase, uint32_t full0,
                                             uint32_t empty0, int wg, int nk) {
    int prev_stage = -1;
#pragma unroll 1
    for (int it = 0; it < nk; ++it) {
        mbar_wait(full0 + 8 * ps.stage, ps.phase);
        uint32_t sa = sbase + ps.stage * STAGE_BYTES + wg * (64 * 128);
        uint32_t sb = sbase + ps.stage * STAGE_BYTES + A_BYTES;
        uint64_t da = make_desc_sw128(sa);
        uint64_t db = make_desc_sw128(sb);
        wgmma_fence();
#pragma unroll
        for (int kk = 0; kk < 4; ++kk) {
            wgmma_m64n256k16(acc, da + (uint64_t)(kk * 2), db + (uint64_t)(kk * 2), (it > 0 || kk > 0) ? 1 : 0);
        }
        wgmma_commit();
        if (prev_stage >= 0) {
            wgmma_wait<1>();
            if ((threadIdx.x & 31) == 0) mbar_arrive(empty0 + 8 * prev_stage);
        }
        prev_stage = ps.stage;
        ps.advance();
    }
    wgmma_wait<0>();
    if ((threadIdx.x & 31) == 0) mbar_arrive(empty0 + 8 * prev_stage);
}

__device__ __forceinline__ void store_tile_bf16(const uint32_t (&pk)[64], uint8_t* stg, __nv_bfloat16* gdst, int ld,
                                                int wg_tid, int bar_id) {
    const int warp = wg_tid >> 5, lane = wg_tid & 31;
    const int r0 = warp * 16 + (lane >> 2);
    const int c0 = (lane & 3) * 2;
#pragma unroll
    for (int j = 0; j < 32; ++j) {
        *reinterpret_cast<uint32_t*>(stg + r0 * STG_PITCH + (j * 8 + c0) * 2) = pk[2 * j];
        *reinterpret_cast<uint32_t*>(stg + (r0 + 8) * STG_PITCH + (j * 8 + c0) * 2) = pk[2 * j + 1];
    }
    named_bar_sync(bar_id, 128);
#pragma unroll
    for (int p = 0; p < 16; ++p) {
        int r = p * 4 + (wg_tid >> 5);
        int cb = (wg_tid & 31) * 16;
        uint4 val = *reinterpret_cast<const uint4*>(stg + r * STG_PITCH + cb);
        *reinterpret_cast<uint4*>(reinterpret_cast<uint8_t*>(gdst + (size_t)r * ld) + cb) = val;
    }
}

__device__ __forceinline__ void counter_wait(unsigned int* ready, unsigned int* passed, unsigned int n_ready,
                                             unsigned int n_wait) {
    unsigned int v;
    long long spins = 0;
    do {
        asm volatile("ld.acquire.gpu.global.u32 %0, [%1];" : "=r"(v) : "l"(ready) : "memory");
    } while (v < n_ready && ++spins < (1ll << 26));
    unsigned int old = atomicAdd(passed, 1u);
    if (old == n_wait - 1) {
        *passed = 0;
        *ready = 0;
        __threadfence();
    }
}

__device__ __forceinline__ void kv_prepass(const Params& p, int s0, int ctid) {
    const int c0 = ctid * 4;
    uint2 kr[19], vr[16];
#pragma unroll
    for (int j = 0; j < 19; ++j) {
        int s = s0 - 3 + j;
        if (s >= 0) kr[j] = __ldg(reinterpret_cast<const uint2*>(p.k + (size_t)s * D_DIM + c0));
        else kr[j] = make_uint2(0, 0);
    }
#pragma unroll
    for (int j = 0; j < 16; ++j) vr[j] = __ldg(reinterpret_cast<const uint2*>(p.v + (size_t)(s0 + j) * D_DIM + c0));
    uint4 w0 = __ldg(reinterpret_cast<const uint4*>(p.shift_k + (size_t)c0 * 4));
    uint4 w1 = __ldg(reinterpret_cast<const uint4*>(p.shift_k + (size_t)c0 * 4 + 8));
    uint32_t wt[2][4];
    wt[0][0] = __byte_perm(w0.x, w0.z, 0x5410); wt[0][1] = __byte_perm(w0.x, w0.z, 0x7632);
    wt[0][2] = __byte_perm(w0.y, w0.w, 0x5410); wt[0][3] = __byte_perm(w0.y, w0.w, 0x7632);
    wt[1][0] = __byte_perm(w1.x, w1.z, 0x5410); wt[1][1] = __byte_perm(w1.x, w1.z, 0x7632);
    wt[1][2] = __byte_perm(w1.y, w1.w, 0x5410); wt[1][3] = __byte_perm(w1.y, w1.w, 0x7632);
#pragma unroll
    for (int pr = 0; pr < 2; ++pr) {
        uint32_t r[16];
#pragma unroll
        for (int j = 0; j < 16; ++j) {
            __nv_bfloat162 k0 = u2b(pr ? kr[j].y : kr[j].x), k1 = u2b(pr ? kr[j + 1].y : kr[j + 1].x);
            __nv_bfloat162 k2 = u2b(pr ? kr[j + 2].y : kr[j + 2].x), k3 = u2b(pr ? kr[j + 3].y : kr[j + 3].x);
            __nv_bfloat162 acc = __hmul2(k0, u2b(wt[pr][3]));
            acc = __hadd2(acc, __hmul2(k1, u2b(wt[pr][2])));
            acc = __hadd2(acc, __hmul2(k2, u2b(wt[pr][1])));
            acc = __hadd2(acc, __hmul2(k3, u2b(wt[pr][0])));
            acc = __hmul2(acc, u2b(pr ? vr[j].y : vr[j].x));
            r[j] = b2u(acc);
        }
        uint32_t lo[8], hi[8];
#pragma unroll
        for (int j = 0; j < 8; ++j) {
            lo[j] = __byte_perm(r[2 * j], r[2 * j + 1], 0x5410);
            hi[j] = __byte_perm(r[2 * j], r[2 * j + 1], 0x7632);
        }
        uint4* d0 = reinterpret_cast<uint4*>(g_kvT + (size_t)(c0 + 2 * pr) * S_LEN + s0);
        uint4* d1 = reinterpret_cast<uint4*>(g_kvT + (size_t)(c0 + 2 * pr + 1) * S_LEN + s0);
        d0[0] = make_uint4(lo[0], lo[1], lo[2], lo[3]);
        d0[1] = make_uint4(lo[4], lo[5], lo[6], lo[7]);
        d1[0] = make_uint4(hi[0], hi[1], hi[2], hi[3]);
        d1[1] = make_uint4(hi[4], hi[5], hi[6], hi[7]);
    }
}

__device__ __forceinline__ void out_postpass(const Params& p, int s0, int ctid) {
    const int c0 = ctid * 4;
    uint2 qr[16];
#pragma unroll
    for (int j = 0; j < 16; ++j) qr[j] = __ldg(reinterpret_cast<const uint2*>(p.q + (size_t)(s0 + j) * D_DIM + c0));
    uint4 yy[4][2];
#pragma unroll
    for (int c = 0; c < 4; ++c) {
        const uint4* src = reinterpret_cast<const uint4*>(g_yT + (size_t)(c0 + c) * S_LEN + s0);
        yy[c][0] = __ldcg(src);
        yy[c][1] = __ldcg(src + 1);
    }
#pragma unroll
    for (int j = 0; j < 16; j += 2) {
        uint32_t y0 = reinterpret_cast<const uint32_t*>(&yy[0][0])[j >> 1], y1 = reinterpret_cast<const uint32_t*>(&yy[1][0])[j >> 1];
        uint32_t y2 = reinterpret_cast<const uint32_t*>(&yy[2][0])[j >> 1], y3 = reinterpret_cast<const uint32_t*>(&yy[3][0])[j >> 1];
        uint2 o;
        o.x = b2u(__hmul2(u2b(qr[j].x), u2b(__byte_perm(y0, y1, 0x5410))));
        o.y = b2u(__hmul2(u2b(qr[j].y), u2b(__byte_perm(y2, y3, 0x5410))));
        *reinterpret_cast<uint2*>(p.out + (size_t)(s0 + j) * 2048 + 1024 + c0) = o;
        o.x = b2u(__hmul2(u2b(qr[j + 1].x), u2b(__byte_perm(y0, y1, 0x7632))));
        o.y = b2u(__hmul2(u2b(qr[j + 1].y), u2b(__byte_perm(y2, y3, 0x7632))));
        *reinterpret_cast<uint2*>(p.out + (size_t)(s0 + j + 1) * 2048 + 1024 + c0) = o;
    }
}

__device__ __forceinline__ void conv_phase(const Params& p, uint8_t* smem, int ch0, int ctid) {
    const int warp = ctid >> 5, lane = ctid & 31;
    __nv_bfloat16* kvs = reinterpret_cast<__nv_bfloat16*>(smem + CONV_KV_OFF) + (size_t)warp * KV_PITCH;
    __nv_bfloat16* rev = reinterpret_cast<__nv_bfloat16*>(smem + CONV_REV_OFF);

    {
        __nv_bfloat16* r0 = rev + (size_t)(warp * 2) * REV_PITCH;
        __nv_bfloat16* r1 = r0 + REV_PITCH;
        const __nv_bfloat16* h = p.ssm_k + (size_t)(ch0 + warp) * S_LEN;
        uint4 hv[8];
#pragma unroll
        for (int it = 0; it < 8; ++it) hv[it] = __ldg(reinterpret_cast<const uint4*>(h + 8 * (lane + 32 * it)));
#pragma unroll
        for (int it = 0; it < 8; ++it) {
            int idx = 8 * (lane + 32 * it);
            const __nv_bfloat16* he = reinterpret_cast<const __nv_bfloat16*>(&hv[it]);
#pragma unroll
            for (int e = 0; e < 8; ++e) {
                r0[REV_Y0 - (idx + e)] = he[e];
                r1[REV_Y0 + 1 - (idx + e)] = he[e];
            }
        }
        if (lane < 24) {
            int idx = -1 - lane;
            r0[REV_Y0 - idx] = __float2bfloat16_rn(0.f);
            r1[REV_Y0 + 1 - idx] = __float2bfloat16_rn(0.f);
        }
    }
    {
        const uint4* src = reinterpret_cast<const uint4*>(g_kvT + (size_t)(ch0 + warp) * S_LEN);
        uint4 t[8];
#pragma unroll
        for (int it = 0; it < 8; ++it) t[it] = __ldcg(src + lane + 32 * it);
#pragma unroll
        for (int it = 0; it < 8; ++it) *reinterpret_cast<uint4*>(kvs + 112 + 8 * (lane + 32 * it)) = t[it];
        if (lane < 14) *reinterpret_cast<uint4*>(kvs + lane * 8) = make_uint4(0, 0, 0, 0);
    }
    __syncwarp();
    TSTAMP(6);
    float acc[16][4];
#pragma unroll
    for (int i = 0; i < 16; ++i) { acc[i][0] = acc[i][1] = acc[i][2] = acc[i][3] = 0.f; }
    const int g = lane >> 2, c2 = (lane & 3) * 2;
    const uint32_t rev_base = smem_u32(rev + (size_t)(warp * 2 + (g & 1)) * REV_PITCH) +
                              2u * (uint32_t)(REV_Y0 + (g & 1) - g + c2);
    const uint32_t kv_base = smem_u32(kvs + 112) + 2u * (uint32_t)(16 * g + c2);
#pragma unroll 1
    for (int a = 0; a < 8; ++a) {
        uint32_t f[16][3];
#pragma unroll
        for (int q = 0; q < 16; ++q) {
            int delta = 16 * a + 128 * q;
            f[q][0] = lds32(rev_base - 2u * (uint32_t)(delta - 8));
            f[q][1] = lds32(rev_base - 2u * (uint32_t)(delta));
            f[q][2] = lds32(rev_base - 2u * (uint32_t)(delta + 8));
        }
        const uint32_t kva = kv_base - 32u * (uint32_t)a;
#pragma unroll
        for (int G = 0; G < 16; ++G) {
            uint32_t b0 = lds32(kva + 256u * G);
            uint32_t b1 = lds32(kva + 256u * G + 16u);
#pragma unroll
            for (int q = 0; q < 16 - G; ++q) {
                mma_bf16_16816(acc[G + q], f[q][1], f[q][2], f[q][0], f[q][1], b0, b1);
            }
        }
    }
    TSTAMP(7);
    __syncwarp();
    {
        const float Dv = __bfloat162float(p.ssm_D[ch0 + warp]);
        __nv_bfloat16* kvc = kvs + 112;
#pragma unroll
        for (int I = 0; I < 16; ++I) {
#pragma unroll
            for (int e = 0; e < 4; ++e) {
                int s = 16 * (8 * I + c2 + (e & 1)) + g + 8 * (e >> 1);
                float kvv = __bfloat162float(kvc[s]);
                float y = rbf(acc[I][e]) + rbf(kvv * Dv);
                kvc[s] = __float2bfloat16_rn(y);
            }
        }
        __syncwarp();
        uint4* dst = reinterpret_cast<uint4*>(g_yT + (size_t)(ch0 + warp) * S_LEN);
#pragma unroll
        for (int it = 0; it < 8; ++it) dst[lane + 32 * it] = *reinterpret_cast<const uint4*>(kvc + 8 * (lane + 32 * it));
    }
}

__global__ void __cluster_dims__(2, 1, 1) __launch_bounds__(NTHREADS, 1)
fused_kernel(const __grid_constant__ CUtensorMap mWre, const __grid_constant__ CUtensorMap mWim,
             const __grid_constant__ CUtensorMap mX, const __grid_constant__ CUtensorMap mAB,
             const __grid_constant__ CUtensorMap mCr, const __grid_constant__ CUtensorMap mCi,
             const Params p) {
    extern __shared__ uint8_t smem_raw[];
    __shared__ __align__(8) uint64_t bars[2 * STAGES];
    uint8_t* smem = smem_raw + ((1024u - (smem_u32(smem_raw) & 1023u)) & 1023u);
    const uint32_t sbase = smem_u32(smem);
    const uint32_t full0 = smem_u32(&bars[0]);
    const uint32_t empty0 = smem_u32(&bars[STAGES]);
    const int tid = threadIdx.x;
    const int wgid = tid >> 7;
    const int bid = blockIdx.x;

    if (tid == 0) {
        for (int i = 0; i < STAGES; ++i) {
            mbar_init(full0 + 8 * i, 1);
            mbar_init(empty0 + 8 * i, 8);
        }
        asm volatile("fence.mbarrier_init.release.cluster;" ::: "memory");
    }
    __syncthreads();

    const int g1_m = bid >> 3, g1_n = bid & 7;
    const int pair = bid >> 1, part = bid & 1;
    const int g2_m = pair >> 2, g2_n = pair & 3;
    const int grp = part * 4 + g2_n;

    if (wgid == 0) {
        if (tid == 0) {
            PipeState ps{0, 0};
            const CUtensorMap* mW = (g1_m < 8) ? &mWre : &mWim;
            gemm_produce(ps, sbase, full0, empty0, mW, &mX, (g1_m & 7) * BM, g1_n * BN, 0, D_DIM / BK);
        }
        if (tid >= 32) {
#pragma unroll 1
            for (int t = tid - 32; t < 256; t += 96) { kv_prepass(p, bid * 16, t); TSTAMP2(8 + t / 96); }
            named_bar_sync(5, 96);
            TSTAMP2(11);
            if (tid == 32) asm volatile("red.release.gpu.global.add.u32 [%0], 1;" ::"l"(&g_sync[0]) : "memory");
        }
        const CUtensorMap* mC = part ? &mCi : &mCr;
        PipeState ps2{0, 0};
        if (tid == 0) {
#pragma unroll 1
            for (int it = g2_n * 8; it < g2_n * 8 + 8; ++it) {
                asm volatile("cp.async.bulk.prefetch.tensor.2d.L2.global [%0, {%1, %2}];" ::"l"((uint64_t)mC),
                             "r"(it * BK), "r"(g2_m * BM) : "memory");
            }
            counter_wait(&g_ready[grp], &g_passed[grp], 16u, 16u);
            asm volatile("fence.proxy.async;" ::: "memory");
            gemm_produce(ps2, sbase, full0, empty0, mC, &mAB, g2_m * BM, grp * BN, 0, 2);
        }
        __syncwarp();
        named_bar_sync(2, NTHREADS);
        if (tid == 0) {
            gemm_produce(ps2, sbase, full0, empty0, mC, &mAB, g2_m * BM, grp * BN, 2, S_LEN / BK);
        }
        if (tid >= 32) {
            if (tid == 32) counter_wait(&g_sync[2], &g_sync[3], 128u, 128u);
            named_bar_sync(5, 96);
#pragma unroll 1
            for (int t = tid - 32; t < 256; t += 96) out_postpass(p, bid * 16, t);
        }
        __syncwarp();
        asm volatile("barrier.cluster.arrive.release.aligned;\n barrier.cluster.wait.acquire.aligned;" ::: "memory");
        asm volatile("barrier.cluster.arrive.release.aligned;\n barrier.cluster.wait.acquire.aligned;" ::: "memory");
    } else {
        const int wg = wgid - 1;
        const int ctid = tid - 128;
        const int wtid = tid & 127;
        PipeState ps{0, 0};
        float acc[128];
        TSTAMP(0);
        gemm_consume(ps, acc, sbase, full0, empty0, wg, D_DIM / BK);
        named_bar_sync(1, 256);
        TSTAMP(1);
        {
            uint32_t pk[64];
#pragma unroll
            for (int i = 0; i < 64; ++i) pk[i] = pack_bf16(acc[2 * i], acc[2 * i + 1]);
            __nv_bfloat16* dst = g_abT + (size_t)(g1_m * BM + wg * 64) * 2048 + g1_n * BN;
            store_tile_bf16(pk, smem + STG1_OFF + wg * STG_WG_BYTES, dst, 2048, wtid, 3 + wg);
        }
        named_bar_sync(1, 256);
        if (ctid == 0) {
            asm volatile("fence.proxy.async;" ::: "memory");
            asm volatile("red.release.gpu.global.add.u32 [%0], 1;" ::"l"(&g_ready[g1_m >> 1]) : "memory");
        }
        TSTAMP(2);
        if (ctid == 0) counter_wait(&g_sync[0], &g_sync[1], 128u, 128u);
        named_bar_sync(1, 256);
        conv_phase(p, smem, bid * 8, ctid);
        asm volatile("fence.proxy.async.shared::cta;" ::: "memory");
        named_bar_sync(2, NTHREADS);
        if (ctid == 0) asm volatile("red.release.gpu.global.add.u32 [%0], 1;" ::"l"(&g_sync[2]) : "memory");
        TSTAMP(3);
#pragma unroll
        for (int i = 0; i < 128; ++i) acc[i] = 0.f;
        gemm_consume(ps, acc, sbase, full0, empty0, wg, S_LEN / BK);
        named_bar_sync(1, 256);
        TSTAMP(4);
        asm volatile("barrier.cluster.arrive.release.aligned;\n barrier.cluster.wait.acquire.aligned;" ::: "memory");
        uint32_t pk[64];
#pragma unroll
        for (int i = 0; i < 64; ++i) pk[i] = pack_bf16(acc[2 * i], acc[2 * i + 1]);
        const uint32_t xbuf = sbase + 2 * STG_WG_BYTES + 1024;
        const bool sender = (wg != part);
        if (sender) {
            uint32_t remote;
            asm volatile("mapa.shared::cluster.u32 %0, %1, %2;" : "=r"(remote) : "r"(xbuf), "r"(part ^ 1));
#pragma unroll
            for (int i = 0; i < 64; ++i) {
                asm volatile("st.shared::cluster.b32 [%0], %1;" ::"r"(remote + (uint32_t)(i * 512 + wtid * 4)), "r"(pk[i]) : "memory");
            }
        }
        asm volatile("barrier.cluster.arrive.release.aligned;\n barrier.cluster.wait.acquire.aligned;" ::: "memory");
        if (!sender) {
#pragma unroll
            for (int i = 0; i < 64; ++i) {
                uint32_t o = lds32(xbuf + (uint32_t)(i * 512 + wtid * 4));
                uint32_t re = part ? o : pk[i];
                uint32_t im = part ? pk[i] : o;
                pk[i] = pack_bf16(bf_lo(re) - bf_lo(im), bf_hi(re) - bf_hi(im));
            }
            __nv_bfloat16* dst = p.out + (size_t)(g2_m * BM + wg * 64) * 2048 + g2_n * BN;
            store_tile_bf16(pk, smem + wg * STG_WG_BYTES, dst, 2048, wtid, 3 + wg);
        }
        TSTAMP(5);
    }
}

typedef CUresult (*PFN_encodeTiled)(CUtensorMap*, CUtensorMapDataType, cuuint32_t, void*, const cuuint64_t*,
                                    const cuuint64_t*, const cuuint32_t*, const cuuint32_t*, CUtensorMapInterleave,
                                    CUtensorMapSwizzle, CUtensorMapL2promotion, CUtensorMapFloatOOBfill);

static void make_map(PFN_encodeTiled enc, CUtensorMap* m, const void* ptr, int rows, int cols, int box_rows) {
    cuuint64_t gdim[2] = {(cuuint64_t)cols, (cuuint64_t)rows};
    cuuint64_t gstr[1] = {(cuuint64_t)cols * 2};
    cuuint32_t box[2] = {64, (cuuint32_t)box_rows};
    cuuint32_t estr[2] = {1, 1};
    enc(m, CU_TENSOR_MAP_DATA_TYPE_BFLOAT16, 2, const_cast<void*>(ptr), gdim, gstr, box, estr,
        CU_TENSOR_MAP_INTERLEAVE_NONE, CU_TENSOR_MAP_SWIZZLE_128B, CU_TENSOR_MAP_L2_PROMOTION_L2_256B,
        CU_TENSOR_MAP_FLOAT_OOB_FILL_NONE);
}

extern "C" void kernel_launch(void* const* d_in, const int* in_sizes, int n_in, void* d_out, int out_size) {
    static PFN_encodeTiled enc = nullptr;
    static bool attr_set = false;
    if (!enc) {
        void* fn = nullptr;
        cudaDriverEntryPointQueryResult qres;
        cudaGetDriverEntryPoint("cuTensorMapEncodeTiled", &fn, cudaEnableDefault, &qres);
        enc = (PFN_encodeTiled)fn;
    }
    if (!attr_set) {
        cudaFuncSetAttribute(fused_kernel, cudaFuncAttributeMaxDynamicSharedMemorySize, SMEM_BYTES);
        attr_set = true;
    }
    void* abT = nullptr;
    cudaGetSymbolAddress(&abT, g_abT);

    CUtensorMap mWre, mWim, mX, mAB, mCr, mCi;
    make_map(enc, &mX, d_in[0], 2048, 1024, BN);
    make_map(enc, &mCr, d_in[1], 2048, 2048, BM);
    make_map(enc, &mCi, d_in[2], 2048, 2048, BM);
    make_map(enc, &mWre, d_in[3], 1024, 1024, BM);
    make_map(enc, &mWim, d_in[4], 1024, 1024, BM);
    make_map(enc, &mAB, abT, 2048, 2048, BN);

    Params p;
    p.q = (const __nv_bfloat16*)d_in[5];
    p.k = (const __nv_bfloat16*)d_in[6];
    p.v = (const __nv_bfloat16*)d_in[7];
    p.shift_k = (const __nv_bfloat16*)d_in[8];
    p.ssm_k = (const __nv_bfloat16*)d_in[9];
    p.ssm_D = (const __nv_bfloat16*)d_in[10];
    p.out = (__nv_bfloat16*)d_out;

    fused_kernel<<<128, NTHREADS, SMEM_BYTES>>>(mWre, mWim, mX, mAB, mCr, mCi, p);
}
```

```cpp
#include <cuda_runtime.h>
#include <cuda_bf16.h>
#include <cuda.h>
#include <stdint.h>

#define S_LEN 2048
#define D_DIM 1024

__device__ __nv_bfloat16 g_abT[2048 * 2048];
__device__ unsigned int g_ready[8];
__device__ unsigned int g_passed[8];
__device__ __nv_bfloat16 g_kvT[1024 * 2048];
__device__ __nv_bfloat16 g_yT[1024 * 2048];
__device__ unsigned int g_sync[4];
#define TSTAMP(i)
#define TSTAMP2(i)

__device__ __forceinline__ uint32_t smem_u32(const void* p) {
    return (uint32_t)__cvta_generic_to_shared(p);
}
__device__ __forceinline__ void mbar_init(uint32_t bar, uint32_t count) {
    asm volatile("mbarrier.init.shared::cta.b64 [%0], %1;" ::"r"(bar), "r"(count));
}
__device__ __forceinline__ void mbar_expect_tx(uint32_t bar, uint32_t bytes) {
    asm volatile("mbarrier.arrive.expect_tx.shared::cta.b64 _, [%0], %1;" ::"r"(bar), "r"(bytes) : "memory");
}
__device__ __forceinline__ void mbar_arrive(uint32_t bar) {
    asm volatile("mbarrier.arrive.shared::cta.b64 _, [%0];" ::"r"(bar) : "memory");
}
__device__ __forceinline__ void mbar_wait(uint32_t bar, uint32_t parity) {
    asm volatile(
        "{\n"
        ".reg .pred p;\n"
        "LAB_WAIT:\n"
        "mbarrier.try_wait.parity.shared::cta.b64 p, [%0], %1;\n"
        "@p bra DONE;\n"
        "bra LAB_WAIT;\n"
        "DONE:\n"
        "}\n" ::"r"(bar), "r"(parity) : "memory");
}
__device__ __forceinline__ void tma_load_2d(uint32_t dst, const CUtensorMap* map, uint32_t bar, int c0, int c1) {
    asm volatile(
        "cp.async.bulk.tensor.2d.shared::cluster.global.mbarrier::complete_tx::bytes [%0], [%1, {%3, %4}], [%2];"
        ::"r"(dst), "l"((uint64_t)map), "r"(bar), "r"(c0), "r"(c1) : "memory");
}
__device__ __forceinline__ void wgmma_fence() { asm volatile("wgmma.fence.sync.aligned;" ::: "memory"); }
__device__ __forceinline__ void wgmma_commit() { asm volatile("wgmma.commit_group.sync.aligned;" ::: "memory"); }
template <int N>
__device__ __forceinline__ void wgmma_wait() { asm volatile("wgmma.wait_group.sync.aligned %0;" ::"n"(N) : "memory"); }

__device__ __forceinline__ uint64_t make_desc_sw128(uint32_t saddr) {
    uint64_t d = 0;
    d |= (uint64_t)((saddr & 0x3FFFF) >> 4);
    d |= (uint64_t)1 << 16;
    d |= (uint64_t)64 << 32;
    d |= (uint64_t)1 << 62;
    return d;
}

#define ACC8(a, i) "+f"(a[i]), "+f"(a[i + 1]), "+f"(a[i + 2]), "+f"(a[i + 3]), "+f"(a[i + 4]), "+f"(a[i + 5]), "+f"(a[i + 6]), "+f"(a[i + 7])

__device__ __forceinline__ void wgmma_m64n256k16(float (&d)[128], uint64_t da, uint64_t db, int scale_d) {
    asm volatile(
        "{\n"
        ".reg .pred p;\n"
        "setp.ne.b32 p, %130, 0;\n"
        "wgmma.mma_async.sync.aligned.m64n256k16.f32.bf16.bf16 "
        "{%0, %1, %2, %3, %4, %5, %6, %7, %8, %9, %10, %11, %12, %13, %14, %15, "
        "%16, %17, %18, %19, %20, %21, %22, %23, %24, %25, %26, %27, %28, %29, %30, %31, "
        "%32, %33, %34, %35, %36, %37, %38, %39, %40, %41, %42, %43, %44, %45, %46, %47, "
        "%48, %49, %50, %51, %52, %53, %54, %55, %56, %57, %58, %59, %60, %61, %62, %63, "
        "%64, %65, %66, %67, %68, %69, %70, %71, %72, %73, %74, %75, %76, %77, %78, %79, "
        "%80, %81, %82, %83, %84, %85, %86, %87, %88, %89, %90, %91, %92, %93, %94, %95, "
        "%96, %97, %98, %99, %100, %101, %102, %103, %104, %105, %106, %107, %108, %109, %110, %111, "
        "%112, %113, %114, %115, %116, %117, %118, %119, %120, %121, %122, %123, %124, %125, %126, %127}, "
        "%128, %129, p, 1, 1, 0, 0;\n"
        "}\n"
        : ACC8(d, 0), ACC8(d, 8), ACC8(d, 16), ACC8(d, 24), ACC8(d, 32), ACC8(d, 40), ACC8(d, 48), ACC8(d, 56),
          ACC8(d, 64), ACC8(d, 72), ACC8(d, 80), ACC8(d, 88), ACC8(d, 96), ACC8(d, 104), ACC8(d, 112), ACC8(d, 120)
        : "l"(da), "l"(db), "r"(scale_d));
}

__device__ __forceinline__ void mma_bf16_16816(float (&c)[4], uint32_t a0, uint32_t a1, uint32_t a2, uint32_t a3,
                                               uint32_t b0, uint32_t b1) {
    asm volatile(
        "mma.sync.aligned.m16n8k16.row.col.f32.bf16.bf16.f32 {%0,%1,%2,%3}, {%4,%5,%6,%7}, {%8,%9}, {%0,%1,%2,%3};"
        : "+f"(c[0]), "+f"(c[1]), "+f"(c[2]), "+f"(c[3])
        : "r"(a0), "r"(a1), "r"(a2), "r"(a3), "r"(b0), "r"(b1));
}

__device__ __forceinline__ uint32_t lds32(uint32_t addr) {
    uint32_t v;
    asm volatile("ld.shared.b32 %0, [%1];" : "=r"(v) : "r"(addr));
    return v;
}
__device__ __forceinline__ uint32_t pack_bf16(float lo, float hi) {
    __nv_bfloat162 t = __floats2bfloat162_rn(lo, hi);
    return *reinterpret_cast<uint32_t*>(&t);
}
__device__ __forceinline__ float bf_lo(uint32_t v) { return __uint_as_float(v << 16); }
__device__ __forceinline__ float bf_hi(uint32_t v) { return __uint_as_float(v & 0xffff0000u); }
__device__ __forceinline__ __nv_bfloat162 u2b(uint32_t v) { return *reinterpret_cast<__nv_bfloat162*>(&v); }
__device__ __forceinline__ uint32_t b2u(__nv_bfloat162 v) { return *reinterpret_cast<uint32_t*>(&v); }
__device__ __forceinline__ float rbf(float x) { return __bfloat162float(__float2bfloat16_rn(x)); }

__device__ __forceinline__ void named_bar_sync(int id, int n) {
    asm volatile("bar.sync %0, %1;" ::"r"(id), "r"(n) : "memory");
}

constexpr int BM = 128, BN = 256, BK = 64, STAGES = 4;
constexpr int A_BYTES = BM * BK * 2;
constexpr int B_BYTES = BN * BK * 2;
constexpr int STAGE_BYTES = A_BYTES + B_BYTES;
constexpr int SMEM_BYTES = STAGES * STAGE_BYTES + 34688 + 1024;
constexpr int NTHREADS = 384;

constexpr int STG_PITCH = 528;
constexpr int STG_WG_BYTES = 64 * STG_PITCH;

constexpr int KV_PITCH = 112 + 2048 + 8;
constexpr int KV_BYTES = 8 * KV_PITCH * 2;
constexpr int REV_PITCH = 2048 + 32 + 8;
constexpr int REV_BYTES = 8 * 2 * REV_PITCH * 2;
constexpr int YS_BYTES = 2048 * 8 * 2;
constexpr int CONV_KV_OFF = STAGES * STAGE_BYTES;
constexpr int CONV_REV_OFF = 2 * STAGE_BYTES;
constexpr int STG1_OFF = 2 * STAGE_BYTES;
constexpr int CONV_YS_OFF = CONV_REV_OFF + REV_BYTES;
static_assert(CONV_REV_OFF + REV_BYTES <= STAGES * STAGE_BYTES && STG1_OFF + 2 * STG_WG_BYTES <= STAGES * STAGE_BYTES && KV_BYTES <= 34688, "conv smem");
constexpr int REV_Y0 = 2048;

struct Params {
    const __nv_bfloat16 *q, *k, *v, *shift_k, *ssm_k, *ssm_D;
    __nv_bfloat16* out;
};

struct PipeState {
    int stage;
    uint32_t phase;
    __device__ __forceinline__ void advance() {
        if (++stage == STAGES) { stage = 0; phase ^= 1; }
    }
};

__device__ __forceinline__ void gemm_produce(PipeState& ps, uint32_t sbase, uint32_t full0, uint32_t empty0,
                                             const CUtensorMap* mA, const CUtensorMap* mB, int arow, int brow, int k0, int nk) {
#pragma unroll 1
    for (int it = k0; it < nk; ++it) {
        mbar_wait(empty0 + 8 * ps.stage, ps.phase ^ 1);
        uint32_t fb = full0 + 8 * ps.stage;
        mbar_expect_tx(fb, STAGE_BYTES);
        uint32_t sa = sbase + ps.stage * STAGE_BYTES;
        tma_load_2d(sa, mA, fb, it * BK, arow);
        tma_load_2d(sa + A_BYTES, mB, fb, it * BK, brow);
        ps.advance();
    }
}

__device__ __forceinline__ void gemm_consume(PipeState& ps, float (&acc)[128], uint32_t sbase, uint32_t full0,
                                             uint32_t empty0, int wg, int nk) {
    int prev_stage = -1;
#pragma unroll 1
    for (int it = 0; it < nk; ++it) {
        mbar_wait(full0 + 8 * ps.stage, ps.phase);
        uint32_t sa = sbase + ps.stage * STAGE_BYTES + wg * (64 * 128);
        uint32_t sb = sbase + ps.stage * STAGE_BYTES + A_BYTES;
        uint64_t da = make_desc_sw128(sa);
        uint64_t db = make_desc_sw128(sb);
        wgmma_fence();
#pragma unroll
        for (int kk = 0; kk < 4; ++kk) {
            wgmma_m64n256k16(acc, da + (uint64_t)(kk * 2), db + (uint64_t)(kk * 2), (it > 0 || kk > 0) ? 1 : 0);
        }
        wgmma_commit();
        if (prev_stage >= 0) {
            wgmma_wait<1>();
            if ((threadIdx.x & 31) == 0) mbar_arrive(empty0 + 8 * prev_stage);
        }
        prev_stage = ps.stage;
        ps.advance();
    }
    wgmma_wait<0>();
    if ((threadIdx.x & 31) == 0) mbar_arrive(empty0 + 8 * prev_stage);
}

__device__ __forceinline__ void store_tile_bf16(const uint32_t (&pk)[64], uint8_t* stg, __nv_bfloat16* gdst, int ld,
                                                int wg_tid, int bar_id) {
    const int warp = wg_tid >> 5, lane = wg_tid & 31;
    const int r0 = warp * 16 + (lane >> 2);
    const int c0 = (lane & 3) * 2;
#pragma unroll
    for (int j = 0; j < 32; ++j) {
        *reinterpret_cast<uint32_t*>(stg + r0 * STG_PITCH + (j * 8 + c0) * 2) = pk[2 * j];
        *reinterpret_cast<uint32_t*>(stg + (r0 + 8) * STG_PITCH + (j * 8 + c0) * 2) = pk[2 * j + 1];
    }
    named_bar_sync(bar_id, 128);
#pragma unroll
    for (int p = 0; p < 16; ++p) {
        int r = p * 4 + (wg_tid >> 5);
        int cb = (wg_tid & 31) * 16;
        uint4 val = *reinterpret_cast<const uint4*>(stg + r * STG_PITCH + cb);
        *reinterpret_cast<uint4*>(reinterpret_cast<uint8_t*>(gdst + (size_t)r * ld) + cb) = val;
    }
}

__device__ __forceinline__ void counter_wait(unsigned int* ready, unsigned int* passed, unsigned int n_ready,
                                             unsigned int n_wait) {
    unsigned int v;
    long long spins = 0;
    do {
        asm volatile("ld.acquire.gpu.global.u32 %0, [%1];" : "=r"(v) : "l"(ready) : "memory");
    } while (v < n_ready && ++spins < (1ll << 26));
    unsigned int old = atomicAdd(passed, 1u);
    if (old == n_wait - 1) {
        *passed = 0;
        *ready = 0;
        __threadfence();
    }
}

__device__ __forceinline__ void kv_prepass(const Params& p, int s0, int ctid) {
    const int c0 = ctid * 4;
    uint2 kr[19], vr[16];
#pragma unroll
    for (int j = 0; j < 19; ++j) {
        int s = s0 - 3 + j;
        if (s >= 0) kr[j] = __ldg(reinterpret_cast<const uint2*>(p.k + (size_t)s * D_DIM + c0));
        else kr[j] = make_uint2(0, 0);
    }
#pragma unroll
    for (int j = 0; j < 16; ++j) vr[j] = __ldg(reinterpret_cast<const uint2*>(p.v + (size_t)(s0 + j) * D_DIM + c0));
    uint4 w0 = __ldg(reinterpret_cast<const uint4*>(p.shift_k + (size_t)c0 * 4));
    uint4 w1 = __ldg(reinterpret_cast<const uint4*>(p.shift_k + (size_t)c0 * 4 + 8));
    uint32_t wt[2][4];
    wt[0][0] = __byte_perm(w0.x, w0.z, 0x5410); wt[0][1] = __byte_perm(w0.x, w0.z, 0x7632);
    wt[0][2] = __byte_perm(w0.y, w0.w, 0x5410); wt[0][3] = __byte_perm(w0.y, w0.w, 0x7632);
    wt[1][0] = __byte_perm(w1.x, w1.z, 0x5410); wt[1][1] = __byte_perm(w1.x, w1.z, 0x7632);
    wt[1][2] = __byte_perm(w1.y, w1.w, 0x5410); wt[1][3] = __byte_perm(w1.y, w1.w, 0x7632);
#pragma unroll
    for (int pr = 0; pr < 2; ++pr) {
        uint32_t r[16];
#pragma unroll
        for (int j = 0; j < 16; ++j) {
            __nv_bfloat162 k0 = u2b(pr ? kr[j].y : kr[j].x), k1 = u2b(pr ? kr[j + 1].y : kr[j + 1].x);
            __nv_bfloat162 k2 = u2b(pr ? kr[j + 2].y : kr[j + 2].x), k3 = u2b(pr ? kr[j + 3].y : kr[j + 3].x);
            __nv_bfloat162 acc = __hmul2(k0, u2b(wt[pr][3]));
            acc = __hadd2(acc, __hmul2(k1, u2b(wt[pr][2])));
            acc = __hadd2(acc, __hmul2(k2, u2b(wt[pr][1])));
            acc = __hadd2(acc, __hmul2(k3, u2b(wt[pr][0])));
            acc = __hmul2(acc, u2b(pr ? vr[j].y : vr[j].x));
            r[j] = b2u(acc);
        }
        uint32_t lo[8], hi[8];
#pragma unroll
        for (int j = 0; j < 8; ++j) {
            lo[j] = __byte_perm(r[2 * j], r[2 * j + 1], 0x5410);
            hi[j] = __byte_perm(r[2 * j], r[2 * j + 1], 0x7632);
        }
        uint4* d0 = reinterpret_cast<uint4*>(g_kvT + (size_t)(c0 + 2 * pr) * S_LEN + s0);
        uint4* d1 = reinterpret_cast<uint4*>(g_kvT + (size_t)(c0 + 2 * pr + 1) * S_LEN + s0);
        d0[0] = make_uint4(lo[0], lo[1], lo[2], lo[3]);
        d0[1] = make_uint4(lo[4], lo[5], lo[6], lo[7]);
        d1[0] = make_uint4(hi[0], hi[1], hi[2], hi[3]);
        d1[1] = make_uint4(hi[4], hi[5], hi[6], hi[7]);
    }
}

__device__ __forceinline__ void out_postpass(const Params& p, int s0, int ctid) {
    const int c0 = ctid * 4;
    uint2 qr[16];
#pragma unroll
    for (int j = 0; j < 16; ++j) qr[j] = __ldg(reinterpret_cast<const uint2*>(p.q + (size_t)(s0 + j) * D_DIM + c0));
    uint4 yy[4][2];
#pragma unroll
    for (int c = 0; c < 4; ++c) {
        const uint4* src = reinterpret_cast<const uint4*>(g_yT + (size_t)(c0 + c) * S_LEN + s0);
        yy[c][0] = __ldcg(src);
        yy[c][1] = __ldcg(src + 1);
    }
#pragma unroll
    for (int j = 0; j < 16; j += 2) {
        uint32_t y0 = reinterpret_cast<const uint32_t*>(&yy[0][0])[j >> 1], y1 = reinterpret_cast<const uint32_t*>(&yy[1][0])[j >> 1];
        uint32_t y2 = reinterpret_cast<const uint32_t*>(&yy[2][0])[j >> 1], y3 = reinterpret_cast<const uint32_t*>(&yy[3][0])[j >> 1];
        uint2 o;
        o.x = b2u(__hmul2(u2b(qr[j].x), u2b(__byte_perm(y0, y1, 0x5410))));
        o.y = b2u(__hmul2(u2b(qr[j].y), u2b(__byte_perm(y2, y3, 0x5410))));
        *reinterpret_cast<uint2*>(p.out + (size_t)(s0 + j) * 2048 + 1024 + c0) = o;
        o.x = b2u(__hmul2(u2b(qr[j + 1].x), u2b(__byte_perm(y0, y1, 0x7632))));
        o.y = b2u(__hmul2(u2b(qr[j + 1].y), u2b(__byte_perm(y2, y3, 0x7632))));
        *reinterpret_cast<uint2*>(p.out + (size_t)(s0 + j + 1) * 2048 + 1024 + c0) = o;
    }
}

__device__ __forceinline__ void conv_phase(const Params& p, uint8_t* smem, int ch0, int ctid, const uint4 (&hv)[8], const uint4 (&t)[8]) {
    const int warp = ctid >> 5, lane = ctid & 31;
    __nv_bfloat16* kvs = reinterpret_cast<__nv_bfloat16*>(smem + CONV_KV_OFF) + (size_t)warp * KV_PITCH;
    __nv_bfloat16* rev = reinterpret_cast<__nv_bfloat16*>(smem + CONV_REV_OFF);

    {
        __nv_bfloat16* r0 = rev + (size_t)(warp * 2) * REV_PITCH;
        __nv_bfloat16* r1 = r0 + REV_PITCH;
#pragma unroll
        for (int it = 0; it < 8; ++it) {
            int idx = 8 * (lane + 32 * it);
            const __nv_bfloat16* he = reinterpret_cast<const __nv_bfloat16*>(&hv[it]);
#pragma unroll
            for (int e = 0; e < 8; ++e) {
                r0[REV_Y0 - (idx + e)] = he[e];
                r1[REV_Y0 + 1 - (idx + e)] = he[e];
            }
        }
        if (lane < 24) {
            int idx = -1 - lane;
            r0[REV_Y0 - idx] = __float2bfloat16_rn(0.f);
            r1[REV_Y0 + 1 - idx] = __float2bfloat16_rn(0.f);
        }
    }
    {
#pragma unroll
        for (int it = 0; it < 8; ++it) *reinterpret_cast<uint4*>(kvs + 112 + 8 * (lane + 32 * it)) = t[it];
        if (lane < 14) *reinterpret_cast<uint4*>(kvs + lane * 8) = make_uint4(0, 0, 0, 0);
    }
    __syncwarp();
    TSTAMP(6);
    float acc[16][4];
#pragma unroll
    for (int i = 0; i < 16; ++i) { acc[i][0] = acc[i][1] = acc[i][2] = acc[i][3] = 0.f; }
    const int g = lane >> 2, c2 = (lane & 3) * 2;
    const uint32_t rev_base = smem_u32(rev + (size_t)(warp * 2 + (g & 1)) * REV_PITCH) +
                              2u * (uint32_t)(REV_Y0 + (g & 1) - g + c2);
    const uint32_t kv_base = smem_u32(kvs + 112) + 2u * (uint32_t)(16 * g + c2);
#pragma unroll 1
    for (int a = 0; a < 8; ++a) {
        uint32_t f[16][3];
#pragma unroll
        for (int q = 0; q < 16; ++q) {
            int delta = 16 * a + 128 * q;
            f[q][0] = lds32(rev_base - 2u * (uint32_t)(delta - 8));
            f[q][1] = lds32(rev_base - 2u * (uint32_t)(delta));
            f[q][2] = lds32(rev_base - 2u * (uint32_t)(delta + 8));
        }
        const uint32_t kva = kv_base - 32u * (uint32_t)a;
#pragma unroll
        for (int G = 0; G < 16; ++G) {
            uint32_t b0 = lds32(kva + 256u * G);
            uint32_t b1 = lds32(kva + 256u * G + 16u);
#pragma unroll
            for (int q = 0; q < 16 - G; ++q) {
                mma_bf16_16816(acc[G + q], f[q][1], f[q][2], f[q][0], f[q][1], b0, b1);
            }
        }
    }
    TSTAMP(7);
    __syncwarp();
    {
        const float Dv = __bfloat162float(p.ssm_D[ch0 + warp]);
        __nv_bfloat16* kvc = kvs + 112;
#pragma unroll
        for (int I = 0; I < 16; ++I) {
#pragma unroll
            for (int e = 0; e < 4; ++e) {
                int s = 16 * (8 * I + c2 + (e & 1)) + g + 8 * (e >> 1);
                float kvv = __bfloat162float(kvc[s]);
                float y = rbf(acc[I][e]) + rbf(kvv * Dv);
                kvc[s] = __float2bfloat16_rn(y);
            }
        }
        __syncwarp();
        uint4* dst = reinterpret_cast<uint4*>(g_yT + (size_t)(ch0 + warp) * S_LEN);
#pragma unroll
        for (int it = 0; it < 8; ++it) dst[lane + 32 * it] = *reinterpret_cast<const uint4*>(kvc + 8 * (lane + 32 * it));
    }
}

__global__ void __cluster_dims__(2, 1, 1) __launch_bounds__(NTHREADS, 1)
fused_kernel(const __grid_constant__ CUtensorMap mWre, const __grid_constant__ CUtensorMap mWim,
             const __grid_constant__ CUtensorMap mX, const __grid_constant__ CUtensorMap mAB,
             const __grid_constant__ CUtensorMap mCr, const __grid_constant__ CUtensorMap mCi,
             const Params p) {
    extern __shared__ uint8_t smem_raw[];
    __shared__ __align__(8) uint64_t bars[2 * STAGES];
    uint8_t* smem = smem_raw + ((1024u - (smem_u32(smem_raw) & 1023u)) & 1023u);
    const uint32_t sbase = smem_u32(smem);
    const uint32_t full0 = smem_u32(&bars[0]);
    const uint32_t empty0 = smem_u32(&bars[STAGES]);
    const int tid = threadIdx.x;
    const int wgid = tid >> 7;
    const int bid = blockIdx.x;

    if (tid == 0) {
        for (int i = 0; i < STAGES; ++i) {
            mbar_init(full0 + 8 * i, 1);
            mbar_init(empty0 + 8 * i, 8);
        }
        asm volatile("fence.mbarrier_init.release.cluster;" ::: "memory");
    }
    __syncthreads();

    const int g1_m = bid >> 3, g1_n = bid & 7;
    const int pair = bid >> 1, part = bid & 1;
    const int g2_m = pair >> 2, g2_n = pair & 3;
    const int grp = part * 4 + g2_n;

    if (wgid == 0) {
        if (tid == 0) {
            PipeState ps{0, 0};
            const CUtensorMap* mW = (g1_m < 8) ? &mWre : &mWim;
            gemm_produce(ps, sbase, full0, empty0, mW, &mX, (g1_m & 7) * BM, g1_n * BN, 0, D_DIM / BK);
        }
        if (tid >= 32) {
#pragma unroll 1
            for (int t = tid - 32; t < 256; t += 96) { kv_prepass(p, bid * 16, t); TSTAMP2(8 + t / 96); }
            named_bar_sync(5, 96);
            TSTAMP2(11);
            if (tid == 32) asm volatile("red.release.gpu.global.add.u32 [%0], 1;" ::"l"(&g_sync[0]) : "memory");
            if (tid < 64) {
                __syncwarp();
                named_bar_sync(6, 288);
                if (tid == 32) {
                    asm volatile("fence.proxy.async;" ::: "memory");
                    asm volatile("red.release.gpu.global.add.u32 [%0], 1;" ::"l"(&g_ready[g1_m >> 1]) : "memory");
                }
             }
        }
        const CUtensorMap* mC = part ? &mCi : &mCr;
        PipeState ps2{0, 0};
        if (tid == 0) {
            counter_wait(&g_ready[grp], &g_passed[grp], 16u, 16u);
            asm volatile("fence.proxy.async;" ::: "memory");
            gemm_produce(ps2, sbase, full0, empty0, mC, &mAB, g2_m * BM, grp * BN, 0, 2);
#pragma unroll 1
            for (int it = g2_n * 8; it < g2_n * 8 + 8; ++it) {
                asm volatile("cp.async.bulk.prefetch.tensor.2d.L2.global [%0, {%1, %2}];" ::"l"((uint64_t)mC),
                             "r"(it * BK), "r"(g2_m * BM) : "memory");
            }
        }
        __syncwarp();
        named_bar_sync(2, NTHREADS);
        if (tid == 0) {
            gemm_produce(ps2, sbase, full0, empty0, mC, &mAB, g2_m * BM, grp * BN, 2, S_LEN / BK);
        }
        if (tid >= 32) {
            if (tid == 32) counter_wait(&g_sync[2], &g_sync[3], 128u, 128u);
            named_bar_sync(5, 96);
#pragma unroll 1
            for (int t = tid - 32; t < 256; t += 96) out_postpass(p, bid * 16, t);
        }
        __syncwarp();
        asm volatile("barrier.cluster.arrive.release.aligned;\n barrier.cluster.wait.acquire.aligned;" ::: "memory");
        asm volatile("barrier.cluster.arrive.release.aligned;\n barrier.cluster.wait.acquire.aligned;" ::: "memory");
    } else {
        const int wg = wgid - 1;
        const int ctid = tid - 128;
        const int wtid = tid & 127;
        PipeState ps{0, 0};
        float acc[128];
        TSTAMP(0);
        gemm_consume(ps, acc, sbase, full0, empty0, wg, D_DIM / BK);
        named_bar_sync(1, 256);
        TSTAMP(1);
        uint4 hv[8], kvr[8];
        {
            uint32_t pk[64];
#pragma unroll
            for (int i = 0; i < 64; ++i) pk[i] = pack_bf16(acc[2 * i], acc[2 * i + 1]);
            if (ctid == 0) counter_wait(&g_sync[0], &g_sync[1], 128u, 128u);
            named_bar_sync(1, 256);
            {
                const int cw = ctid >> 5, cl = ctid & 31;
                const uint4* hs = reinterpret_cast<const uint4*>(p.ssm_k + (size_t)(bid * 8 + cw) * S_LEN);
                const uint4* ks = reinterpret_cast<const uint4*>(g_kvT + (size_t)(bid * 8 + cw) * S_LEN);
#pragma unroll
                for (int it = 0; it < 8; ++it) { hv[it] = __ldg(hs + cl + 32 * it); kvr[it] = __ldcg(ks + cl + 32 * it); }
            }
            __nv_bfloat16* dst = g_abT + (size_t)(g1_m * BM + wg * 64) * 2048 + g1_n * BN;
            store_tile_bf16(pk, smem + STG1_OFF + wg * STG_WG_BYTES, dst, 2048, wtid, 3 + wg);
        }
        asm volatile("bar.arrive 6, 288;" ::: "memory");
        TSTAMP(2);
        named_bar_sync(1, 256);
        conv_phase(p, smem, bid * 8, ctid, hv, kvr);
        asm volatile("fence.proxy.async.shared::cta;" ::: "memory");
        named_bar_sync(2, NTHREADS);
        if (ctid == 0) asm volatile("red.release.gpu.global.add.u32 [%0], 1;" ::"l"(&g_sync[2]) : "memory");
        TSTAMP(3);
#pragma unroll
        for (int i = 0; i < 128; ++i) acc[i] = 0.f;
        gemm_consume(ps, acc, sbase, full0, empty0, wg, S_LEN / BK);
        named_bar_sync(1, 256);
        TSTAMP(4);
        asm volatile("barrier.cluster.arrive.release.aligned;\n barrier.cluster.wait.acquire.aligned;" ::: "memory");
        uint32_t pk[64];
#pragma unroll
        for (int i = 0; i < 64; ++i) pk[i] = pack_bf16(acc[2 * i], acc[2 * i + 1]);
        const uint32_t xbuf = sbase + 2 * STG_WG_BYTES + 1024;
        const bool sender = (wg != part);
        if (sender) {
            uint32_t remote;
            asm volatile("mapa.shared::cluster.u32 %0, %1, %2;" : "=r"(remote) : "r"(xbuf), "r"(part ^ 1));
#pragma unroll
            for (int i = 0; i < 64; ++i) {
                asm volatile("st.shared::cluster.b32 [%0], %1;" ::"r"(remote + (uint32_t)(i * 512 + wtid * 4)), "r"(pk[i]) : "memory");
            }
        }
        asm volatile("barrier.cluster.arrive.release.aligned;\n barrier.cluster.wait.acquire.aligned;" ::: "memory");
        if (!sender) {
#pragma unroll
            for (int i = 0; i < 64; ++i) {
                uint32_t o = lds32(xbuf + (uint32_t)(i * 512 + wtid * 4));
                uint32_t re = part ? o : pk[i];
                uint32_t im = part ? pk[i] : o;
                pk[i] = pack_bf16(bf_lo(re) - bf_lo(im), bf_hi(re) - bf_hi(im));
            }
            __nv_bfloat16* dst = p.out + (size_t)(g2_m * BM + wg * 64) * 2048 + g2_n * BN;
            store_tile_bf16(pk, smem + wg * STG_WG_BYTES, dst, 2048, wtid, 3 + wg);
        }
        TSTAMP(5);
    }
}

typedef CUresult (*PFN_encodeTiled)(CUtensorMap*, CUtensorMapDataType, cuuint32_t, void*, const cuuint64_t*,
                                    const cuuint64_t*, const cuuint32_t*, const cuuint32_t*, CUtensorMapInterleave,
                                    CUtensorMapSwizzle, CUtensorMapL2promotion, CUtensorMapFloatOOBfill);

static void make_map(PFN_encodeTiled enc, CUtensorMap* m, const void* ptr, int rows, int cols, int box_rows) {
    cuuint64_t gdim[2] = {(cuuint64_t)cols, (cuuint64_t)rows};
    cuuint64_t gstr[1] = {(cuuint64_t)cols * 2};
    cuuint32_t box[2] = {64, (cuuint32_t)box_rows};
    cuuint32_t estr[2] = {1, 1};
    enc(m, CU_TENSOR_MAP_DATA_TYPE_BFLOAT16, 2, const_cast<void*>(ptr), gdim, gstr, box, estr,
        CU_TENSOR_MAP_INTERLEAVE_NONE, CU_TENSOR_MAP_SWIZZLE_128B, CU_TENSOR_MAP_L2_PROMOTION_L2_256B,
        CU_TENSOR_MAP_FLOAT_OOB_FILL_NONE);
}

extern "C" void kernel_launch(void* const* d_in, const int* in_sizes, int n_in, void* d_out, int out_size) {
    static PFN_encodeTiled enc = nullptr;
    static bool attr_set = false;
    if (!enc) {
        void* fn = nullptr;
        cudaDriverEntryPointQueryResult qres;
        cudaGetDriverEntryPoint("cuTensorMapEncodeTiled", &fn, cudaEnableDefault, &qres);
        enc = (PFN_encodeTiled)fn;
    }
    if (!attr_set) {
        cudaFuncSetAttribute(fused_kernel, cudaFuncAttributeMaxDynamicSharedMemorySize, SMEM_BYTES);
        attr_set = true;
    }
    void* abT = nullptr;
    cudaGetSymbolAddress(&abT, g_abT);

    CUtensorMap mWre, mWim, mX, mAB, mCr, mCi;
    make_map(enc, &mX, d_in[0], 2048, 1024, BN);
    make_map(enc, &mCr, d_in[1], 2048, 2048, BM);
    make_map(enc, &mCi, d_in[2], 2048, 2048, BM);
    make_map(enc, &mWre, d_in[3], 1024, 1024, BM);
    make_map(enc, &mWim, d_in[4], 1024, 1024, BM);
    make_map(enc, &mAB, abT, 2048, 2048, BN);

    Params p;
    p.q = (const __nv_bfloat16*)d_in[5];
    p.k = (const __nv_bfloat16*)d_in[6];
    p.v = (const __nv_bfloat16*)d_in[7];
    p.shift_k = (const __nv_bfloat16*)d_in[8];
    p.ssm_k = (const __nv_bfloat16*)d_in[9];
    p.ssm_D = (const __nv_bfloat16*)d_in[10];
    p.out = (__nv_bfloat16*)d_out;

    fused_kernel<<<128, NTHREADS, SMEM_BYTES>>>(mWre, mWim, mX, mAB, mCr, mCi, p);
}
```

```cpp
#include <cuda_runtime.h>
#include <cuda_bf16.h>
#include <cuda.h>
#include <stdint.h>

#define S_LEN 2048
#define D_DIM 1024

__device__ __nv_bfloat16 g_abT[2048 * 2048];
__device__ unsigned int g_ready[8];
__device__ unsigned int g_passed[8];
__device__ __nv_bfloat16 g_kvT[1024 * 2048];
__device__ __nv_bfloat16 g_yT[1024 * 2048];
__device__ unsigned int g_sync[4];
#define TSTAMP(i)
#define TSTAMP2(i)

__device__ __forceinline__ uint32_t smem_u32(const void* p) {
    return (uint32_t)__cvta_generic_to_shared(p);
}
__device__ __forceinline__ void mbar_init(uint32_t bar, uint32_t count) {
    asm volatile("mbarrier.init.shared::cta.b64 [%0], %1;" ::"r"(bar), "r"(count));
}
__device__ __forceinline__ void mbar_expect_tx(uint32_t bar, uint32_t bytes) {
    asm volatile("mbarrier.arrive.expect_tx.shared::cta.b64 _, [%0], %1;" ::"r"(bar), "r"(bytes) : "memory");
}
__device__ __forceinline__ void mbar_arrive(uint32_t bar) {
    asm volatile("mbarrier.arrive.shared::cta.b64 _, [%0];" ::"r"(bar) : "memory");
}
__device__ __forceinline__ void mbar_wait(uint32_t bar, uint32_t parity) {
    asm volatile(
        "{\n"
        ".reg .pred p;\n"
        "LAB_WAIT:\n"
        "mbarrier.try_wait.parity.shared::cta.b64 p, [%0], %1;\n"
        "@p bra DONE;\n"
        "bra LAB_WAIT;\n"
        "DONE:\n"
        "}\n" ::"r"(bar), "r"(parity) : "memory");
}
__device__ __forceinline__ void tma_load_2d(uint32_t dst, const CUtensorMap* map, uint32_t bar, int c0, int c1) {
    asm volatile(
        "cp.async.bulk.tensor.2d.shared::cluster.global.mbarrier::complete_tx::bytes [%0], [%1, {%3, %4}], [%2];"
        ::"r"(dst), "l"((uint64_t)map), "r"(bar), "r"(c0), "r"(c1) : "memory");
}
__device__ __forceinline__ void tma_load_2d_mc(uint32_t dst, const CUtensorMap* map, uint32_t bar, int c0, int c1,
                                               uint16_t mask) {
    asm volatile(
        "cp.async.bulk.tensor.2d.shared::cluster.global.mbarrier::complete_tx::bytes.multicast::cluster "
        "[%0], [%1, {%3, %4}], [%2], %5;"
        ::"r"(dst), "l"((uint64_t)map), "r"(bar), "r"(c0), "r"(c1), "h"(mask) : "memory");
}
__device__ __forceinline__ uint32_t mapa_u32(uint32_t addr, uint32_t rank) {
    uint32_t r;
    asm volatile("mapa.shared::cluster.u32 %0, %1, %2;" : "=r"(r) : "r"(addr), "r"(rank));
    return r;
}
__device__ __forceinline__ void mbar_arrive_cluster(uint32_t remote_bar) {
    asm volatile("mbarrier.arrive.shared::cluster.b64 _, [%0];" ::"r"(remote_bar) : "memory");
}
__device__ __forceinline__ void cluster_sync_all() {
    asm volatile("barrier.cluster.arrive.release.aligned;\n barrier.cluster.wait.acquire.aligned;" ::: "memory");
}
__device__ __forceinline__ void wgmma_fence() { asm volatile("wgmma.fence.sync.aligned;" ::: "memory"); }
__device__ __forceinline__ void wgmma_commit() { asm volatile("wgmma.commit_group.sync.aligned;" ::: "memory"); }
template <int N>
__device__ __forceinline__ void wgmma_wait() { asm volatile("wgmma.wait_group.sync.aligned %0;" ::"n"(N) : "memory"); }

__device__ __forceinline__ uint64_t make_desc_sw128(uint32_t saddr) {
    uint64_t d = 0;
    d |= (uint64_t)((saddr & 0x3FFFF) >> 4);
    d |= (uint64_t)1 << 16;
    d |= (uint64_t)64 << 32;
    d |= (uint64_t)1 << 62;
    return d;
}

#define ACC8(a, i) "+f"(a[i]), "+f"(a[i + 1]), "+f"(a[i + 2]), "+f"(a[i + 3]), "+f"(a[i + 4]), "+f"(a[i + 5]), "+f"(a[i + 6]), "+f"(a[i + 7])

__device__ __forceinline__ void wgmma_m64n256k16(float (&d)[128], uint64_t da, uint64_t db, int scale_d) {
    asm volatile(
        "{\n"
        ".reg .pred p;\n"
        "setp.ne.b32 p, %130, 0;\n"
        "wgmma.mma_async.sync.aligned.m64n256k16.f32.bf16.bf16 "
        "{%0, %1, %2, %3, %4, %5, %6, %7, %8, %9, %10, %11, %12, %13, %14, %15, "
        "%16, %17, %18, %19, %20, %21, %22, %23, %24, %25, %26, %27, %28, %29, %30, %31, "
        "%32, %33, %34, %35, %36, %37, %38, %39, %40, %41, %42, %43, %44, %45, %46, %47, "
        "%48, %49, %50, %51, %52, %53, %54, %55, %56, %57, %58, %59, %60, %61, %62, %63, "
        "%64, %65, %66, %67, %68, %69, %70, %71, %72, %73, %74, %75, %76, %77, %78, %79, "
        "%80, %81, %82, %83, %84, %85, %86, %87, %88, %89, %90, %91, %92, %93, %94, %95, "
        "%96, %97, %98, %99, %100, %101, %102, %103, %104, %105, %106, %107, %108, %109, %110, %111, "
        "%112, %113, %114, %115, %116, %117, %118, %119, %120, %121, %122, %123, %124, %125, %126, %127}, "
        "%128, %129, p, 1, 1, 0, 0;\n"
        "}\n"
        : ACC8(d, 0), ACC8(d, 8), ACC8(d, 16), ACC8(d, 24), ACC8(d, 32), ACC8(d, 40), ACC8(d, 48), ACC8(d, 56),
          ACC8(d, 64), ACC8(d, 72), ACC8(d, 80), ACC8(d, 88), ACC8(d, 96), ACC8(d, 104), ACC8(d, 112), ACC8(d, 120)
        : "l"(da), "l"(db), "r"(scale_d));
}

__device__ __forceinline__ void mma_bf16_16816(float (&c)[4], uint32_t a0, uint32_t a1, uint32_t a2, uint32_t a3,
                                               uint32_t b0, uint32_t b1) {
    asm volatile(
        "mma.sync.aligned.m16n8k16.row.col.f32.bf16.bf16.f32 {%0,%1,%2,%3}, {%4,%5,%6,%7}, {%8,%9}, {%0,%1,%2,%3};"
        : "+f"(c[0]), "+f"(c[1]), "+f"(c[2]), "+f"(c[3])
        : "r"(a0), "r"(a1), "r"(a2), "r"(a3), "r"(b0), "r"(b1));
}

__device__ __forceinline__ uint32_t lds32(uint32_t addr) {
    uint32_t v;
    asm volatile("ld.shared.b32 %0, [%1];" : "=r"(v) : "r"(addr));
    return v;
}
__device__ __forceinline__ uint32_t pack_bf16(float lo, float hi) {
    __nv_bfloat162 t = __floats2bfloat162_rn(lo, hi);
    return *reinterpret_cast<uint32_t*>(&t);
}
__device__ __forceinline__ float bf_lo(uint32_t v) { return __uint_as_float(v << 16); }
__device__ __forceinline__ float bf_hi(uint32_t v) { return __uint_as_float(v & 0xffff0000u); }
__device__ __forceinline__ __nv_bfloat162 u2b(uint32_t v) { return *reinterpret_cast<__nv_bfloat162*>(&v); }
__device__ __forceinline__ uint32_t b2u(__nv_bfloat162 v) { return *reinterpret_cast<uint32_t*>(&v); }
__device__ __forceinline__ float rbf(float x) { return __bfloat162float(__float2bfloat16_rn(x)); }

__device__ __forceinline__ void named_bar_sync(int id, int n) {
    asm volatile("bar.sync %0, %1;" ::"r"(id), "r"(n) : "memory");
}

constexpr int BM = 128, BN = 256, BK = 64, STAGES = 4;
constexpr int A_BYTES = BM * BK * 2;
constexpr int B_BYTES = BN * BK * 2;
constexpr int STAGE_BYTES = A_BYTES + B_BYTES;
constexpr int SMEM_BYTES = STAGES * STAGE_BYTES + 34688 + 1024;
constexpr int NTHREADS = 384;

constexpr int STG_PITCH = 528;
constexpr int STG_WG_BYTES = 64 * STG_PITCH;

constexpr int KV_PITCH = 112 + 2048 + 8;
constexpr int KV_BYTES = 8 * KV_PITCH * 2;
constexpr int REV_PITCH = 2048 + 32 + 8;
constexpr int REV_BYTES = 8 * 2 * REV_PITCH * 2;
constexpr int YS_BYTES = 2048 * 8 * 2;
constexpr int CONV_KV_OFF = STAGES * STAGE_BYTES;
constexpr int CONV_REV_OFF = 2 * STAGE_BYTES;
constexpr int STG1_OFF = 2 * STAGE_BYTES;
constexpr int CONV_YS_OFF = CONV_REV_OFF + REV_BYTES;
static_assert(CONV_REV_OFF + REV_BYTES <= STAGES * STAGE_BYTES && STG1_OFF + 2 * STG_WG_BYTES <= STAGES * STAGE_BYTES && KV_BYTES <= 34688, "conv smem");
constexpr int REV_Y0 = 2048;

struct Params {
    const __nv_bfloat16 *q, *k, *v, *shift_k, *ssm_k, *ssm_D;
    __nv_bfloat16* out;
};

struct PipeState {
    int stage;
    uint32_t phase;
    __device__ __forceinline__ void advance() {
        if (++stage == STAGES) { stage = 0; phase ^= 1; }
    }
};

template <bool B_MC>
__device__ __forceinline__ void gemm_produce(PipeState& ps, uint32_t sbase, uint32_t full0, uint32_t empty0,
                                             const CUtensorMap* mA, const CUtensorMap* mB, int arow, int brow,
                                             int ahalf, int bhalf, uint16_t maskA, uint16_t maskB, int k0, int nk) {
#pragma unroll 1
    for (int it = k0; it < nk; ++it) {
        mbar_wait(empty0 + 8 * ps.stage, ps.phase ^ 1);
        uint32_t fb = full0 + 8 * ps.stage;
        mbar_expect_tx(fb, STAGE_BYTES);
        uint32_t sa = sbase + ps.stage * STAGE_BYTES;
        tma_load_2d(sa, mA, fb, it * BK, arow);
        tma_load_2d(sa + A_BYTES / 2, mA, fb, it * BK, arow + BM / 2);
        if (B_MC) {
            tma_load_2d_mc(sa + A_BYTES + bhalf * (B_BYTES / 2), mB, fb, it * BK, brow + bhalf * (BN / 2), maskB);
        } else {
            tma_load_2d(sa + A_BYTES, mB, fb, it * BK, brow);
            tma_load_2d(sa + A_BYTES + B_BYTES / 2, mB, fb, it * BK, brow + BN / 2);
        }
        ps.advance();
    }
}

__device__ __forceinline__ void release_stage(uint32_t empty0, uint32_t emptyA, uint32_t emptyB, int stage) {
    if ((threadIdx.x & 31) == 0) {
        mbar_arrive(empty0 + 8 * stage);
        mbar_arrive_cluster(emptyB + 8 * stage);
    }
}

__device__ __forceinline__ void gemm_consume(PipeState& ps, float (&acc)[128], uint32_t sbase, uint32_t full0,
                                             uint32_t empty0, uint32_t emptyA, uint32_t emptyB, int wg, int nk,
                                             int n_hold) {
    int prev_stage = -1;
#pragma unroll 1
    for (int it = 0; it < nk; ++it) {
        mbar_wait(full0 + 8 * ps.stage, ps.phase);
        uint32_t sa = sbase + ps.stage * STAGE_BYTES + wg * (64 * 128);
        uint32_t sb = sbase + ps.stage * STAGE_BYTES + A_BYTES;
        uint64_t da = make_desc_sw128(sa);
        uint64_t db = make_desc_sw128(sb);
        wgmma_fence();
#pragma unroll
        for (int kk = 0; kk < 4; ++kk) {
            wgmma_m64n256k16(acc, da + (uint64_t)(kk * 2), db + (uint64_t)(kk * 2), (it > 0 || kk > 0) ? 1 : 0);
        }
        wgmma_commit();
        if (prev_stage >= 0) {
            wgmma_wait<1>();
            if (it - 1 < nk - n_hold) release_stage(empty0, emptyA, emptyB, prev_stage);
        }
        prev_stage = ps.stage;
        ps.advance();
    }
    wgmma_wait<0>();
    if (n_hold == 0) release_stage(empty0, emptyA, emptyB, prev_stage);
}

__device__ __forceinline__ void store_tile_bf16(const uint32_t (&pk)[64], uint8_t* stg, __nv_bfloat16* gdst, int ld,
                                                int wg_tid, int bar_id) {
    const int warp = wg_tid >> 5, lane = wg_tid & 31;
    const int r0 = warp * 16 + (lane >> 2);
    const int c0 = (lane & 3) * 2;
#pragma unroll
    for (int j = 0; j < 32; ++j) {
        *reinterpret_cast<uint32_t*>(stg + r0 * STG_PITCH + (j * 8 + c0) * 2) = pk[2 * j];
        *reinterpret_cast<uint32_t*>(stg + (r0 + 8) * STG_PITCH + (j * 8 + c0) * 2) = pk[2 * j + 1];
    }
    named_bar_sync(bar_id, 128);
#pragma unroll
    for (int p = 0; p < 16; ++p) {
        int r = p * 4 + (wg_tid >> 5);
        int cb = (wg_tid & 31) * 16;
        uint4 val = *reinterpret_cast<const uint4*>(stg + r * STG_PITCH + cb);
        *reinterpret_cast<uint4*>(reinterpret_cast<uint8_t*>(gdst + (size_t)r * ld) + cb) = val;
    }
}

__device__ __forceinline__ void counter_wait(unsigned int* ready, unsigned int* passed, unsigned int n_ready,
                                             unsigned int n_wait) {
    unsigned int v;
    long long spins = 0;
    do {
        asm volatile("ld.acquire.gpu.global.u32 %0, [%1];" : "=r"(v) : "l"(ready) : "memory");
    } while (v < n_ready && ++spins < (1ll << 26));
    unsigned int old = atomicAdd(passed, 1u);
    if (old == n_wait - 1) {
        *passed = 0;
        *ready = 0;
        __threadfence();
    }
}

__device__ __forceinline__ void kv_prepass(const Params& p, int s0, int ctid) {
    const int c0 = ctid * 4;
    uint2 kr[19], vr[16];
#pragma unroll
    for (int j = 0; j < 19; ++j) {
        int s = s0 - 3 + j;
        if (s >= 0) kr[j] = __ldg(reinterpret_cast<const uint2*>(p.k + (size_t)s * D_DIM + c0));
        else kr[j] = make_uint2(0, 0);
    }
#pragma unroll
    for (int j = 0; j < 16; ++j) vr[j] = __ldg(reinterpret_cast<const uint2*>(p.v + (size_t)(s0 + j) * D_DIM + c0));
    uint4 w0 = __ldg(reinterpret_cast<const uint4*>(p.shift_k + (size_t)c0 * 4));
    uint4 w1 = __ldg(reinterpret_cast<const uint4*>(p.shift_k + (size_t)c0 * 4 + 8));
    uint32_t wt[2][4];
    wt[0][0] = __byte_perm(w0.x, w0.z, 0x5410); wt[0][1] = __byte_perm(w0.x, w0.z, 0x7632);
    wt[0][2] = __byte_perm(w0.y, w0.w, 0x5410); wt[0][3] = __byte_perm(w0.y, w0.w, 0x7632);
    wt[1][0] = __byte_perm(w1.x, w1.z, 0x5410); wt[1][1] = __byte_perm(w1.x, w1.z, 0x7632);
    wt[1][2] = __byte_perm(w1.y, w1.w, 0x5410); wt[1][3] = __byte_perm(w1.y, w1.w, 0x7632);
#pragma unroll
    for (int pr = 0; pr < 2; ++pr) {
        uint32_t r[16];
#pragma unroll
        for (int j = 0; j < 16; ++j) {
            __nv_bfloat162 k0 = u2b(pr ? kr[j].y : kr[j].x), k1 = u2b(pr ? kr[j + 1].y : kr[j + 1].x);
            __nv_bfloat162 k2 = u2b(pr ? kr[j + 2].y : kr[j + 2].x), k3 = u2b(pr ? kr[j + 3].y : kr[j + 3].x);
            __nv_bfloat162 acc = __hmul2(k0, u2b(wt[pr][3]));
            acc = __hadd2(acc, __hmul2(k1, u2b(wt[pr][2])));
            acc = __hadd2(acc, __hmul2(k2, u2b(wt[pr][1])));
            acc = __hadd2(acc, __hmul2(k3, u2b(wt[pr][0])));
            acc = __hmul2(acc, u2b(pr ? vr[j].y : vr[j].x));
            r[j] = b2u(acc);
        }
        uint32_t lo[8], hi[8];
#pragma unroll
        for (int j = 0; j < 8; ++j) {
            lo[j] = __byte_perm(r[2 * j], r[2 * j + 1], 0x5410);
            hi[j] = __byte_perm(r[2 * j], r[2 * j + 1], 0x7632);
        }
        uint4* d0 = reinterpret_cast<uint4*>(g_kvT + (size_t)(c0 + 2 * pr) * S_LEN + s0);
        uint4* d1 = reinterpret_cast<uint4*>(g_kvT + (size_t)(c0 + 2 * pr + 1) * S_LEN + s0);
        d0[0] = make_uint4(lo[0], lo[1], lo[2], lo[3]);
        d0[1] = make_uint4(lo[4], lo[5], lo[6], lo[7]);
        d1[0] = make_uint4(hi[0], hi[1], hi[2], hi[3]);
        d1[1] = make_uint4(hi[4], hi[5], hi[6], hi[7]);
    }
}

__device__ __forceinline__ void out_postpass(const Params& p, int s0, int ctid) {
    const int c0 = ctid * 4;
    uint2 qr[16];
#pragma unroll
    for (int j = 0; j < 16; ++j) qr[j] = __ldg(reinterpret_cast<const uint2*>(p.q + (size_t)(s0 + j) * D_DIM + c0));
    uint4 yy[4][2];
#pragma unroll
    for (int c = 0; c < 4; ++c) {
        const uint4* src = reinterpret_cast<const uint4*>(g_yT + (size_t)(c0 + c) * S_LEN + s0);
        yy[c][0] = __ldcg(src);
        yy[c][1] = __ldcg(src + 1);
    }
#pragma unroll
    for (int j = 0; j < 16; j += 2) {
        uint32_t y0 = reinterpret_cast<const uint32_t*>(&yy[0][0])[j >> 1], y1 = reinterpret_cast<const uint32_t*>(&yy[1][0])[j >> 1];
        uint32_t y2 = reinterpret_cast<const uint32_t*>(&yy[2][0])[j >> 1], y3 = reinterpret_cast<const uint32_t*>(&yy[3][0])[j >> 1];
        uint2 o;
        o.x = b2u(__hmul2(u2b(qr[j].x), u2b(__byte_perm(y0, y1, 0x5410))));
        o.y = b2u(__hmul2(u2b(qr[j].y), u2b(__byte_perm(y2, y3, 0x5410))));
        *reinterpret_cast<uint2*>(p.out + (size_t)(s0 + j) * 2048 + 1024 + c0) = o;
        o.x = b2u(__hmul2(u2b(qr[j + 1].x), u2b(__byte_perm(y0, y1, 0x7632))));
        o.y = b2u(__hmul2(u2b(qr[j + 1].y), u2b(__byte_perm(y2, y3, 0x7632))));
        *reinterpret_cast<uint2*>(p.out + (size_t)(s0 + j + 1) * 2048 + 1024 + c0) = o;
    }
}

__device__ __forceinline__ void conv_phase(const Params& p, uint8_t* smem, int ch0, int ctid, const uint4 (&hv)[8], const uint4 (&t)[8]) {
    const int warp = ctid >> 5, lane = ctid & 31;
    __nv_bfloat16* kvs = reinterpret_cast<__nv_bfloat16*>(smem + CONV_KV_OFF) + (size_t)warp * KV_PITCH;
    __nv_bfloat16* rev = reinterpret_cast<__nv_bfloat16*>(smem + CONV_REV_OFF);

    {
        __nv_bfloat16* r0 = rev + (size_t)(warp * 2) * REV_PITCH;
        __nv_bfloat16* r1 = r0 + REV_PITCH;
#pragma unroll
        for (int it = 0; it < 8; ++it) {
            int idx = 8 * (lane + 32 * it);
            const __nv_bfloat16* he = reinterpret_cast<const __nv_bfloat16*>(&hv[it]);
#pragma unroll
            for (int e = 0; e < 8; ++e) {
                r0[REV_Y0 - (idx + e)] = he[e];
                r1[REV_Y0 + 1 - (idx + e)] = he[e];
            }
        }
        if (lane < 24) {
            int idx = -1 - lane;
            r0[REV_Y0 - idx] = __float2bfloat16_rn(0.f);
            r1[REV_Y0 + 1 - idx] = __float2bfloat16_rn(0.f);
        }
    }
    {
#pragma unroll
        for (int it = 0; it < 8; ++it) *reinterpret_cast<uint4*>(kvs + 112 + 8 * (lane + 32 * it)) = t[it];
        if (lane < 14) *reinterpret_cast<uint4*>(kvs + lane * 8) = make_uint4(0, 0, 0, 0);
    }
    __syncwarp();
    TSTAMP(6);
    float acc[16][4];
#pragma unroll
    for (int i = 0; i < 16; ++i) { acc[i][0] = acc[i][1] = acc[i][2] = acc[i][3] = 0.f; }
    const int g = lane >> 2, c2 = (lane & 3) * 2;
    const uint32_t rev_base = smem_u32(rev + (size_t)(warp * 2 + (g & 1)) * REV_PITCH) +
                              2u * (uint32_t)(REV_Y0 + (g & 1) - g + c2);
    const uint32_t kv_base = smem_u32(kvs + 112) + 2u * (uint32_t)(16 * g + c2);
#pragma unroll 1
    for (int a = 0; a < 8; ++a) {
        uint32_t f[16][3];
#pragma unroll
        for (int q = 0; q < 16; ++q) {
            int delta = 16 * a + 128 * q;
            f[q][0] = lds32(rev_base - 2u * (uint32_t)(delta - 8));
            f[q][1] = lds32(rev_base - 2u * (uint32_t)(delta));
            f[q][2] = lds32(rev_base - 2u * (uint32_t)(delta + 8));
        }
        const uint32_t kva = kv_base - 32u * (uint32_t)a;
#pragma unroll
        for (int G = 0; G < 16; ++G) {
            uint32_t b0 = lds32(kva + 256u * G);
            uint32_t b1 = lds32(kva + 256u * G + 16u);
#pragma unroll
            for (int q = 0; q < 16 - G; ++q) {
                mma_bf16_16816(acc[G + q], f[q][1], f[q][2], f[q][0], f[q][1], b0, b1);
            }
        }
    }
    TSTAMP(7);
    __syncwarp();
    {
        const float Dv = __bfloat162float(p.ssm_D[ch0 + warp]);
        __nv_bfloat16* kvc = kvs + 112;
#pragma unroll
        for (int I = 0; I < 16; ++I) {
#pragma unroll
            for (int e = 0; e < 4; ++e) {
                int s = 16 * (8 * I + c2 + (e & 1)) + g + 8 * (e >> 1);
                float kvv = __bfloat162float(kvc[s]);
                float y = rbf(acc[I][e]) + rbf(kvv * Dv);
                kvc[s] = __float2bfloat16_rn(y);
            }
        }
        __syncwarp();
        uint4* dst = reinterpret_cast<uint4*>(g_yT + (size_t)(ch0 + warp) * S_LEN);
#pragma unroll
        for (int it = 0; it < 8; ++it) dst[lane + 32 * it] = *reinterpret_cast<const uint4*>(kvc + 8 * (lane + 32 * it));
    }
}

__global__ void __cluster_dims__(2, 1, 1) __launch_bounds__(NTHREADS, 1)
fused_kernel(const __grid_constant__ CUtensorMap mWre, const __grid_constant__ CUtensorMap mWim,
             const __grid_constant__ CUtensorMap mX, const __grid_constant__ CUtensorMap mAB,
             const __grid_constant__ CUtensorMap mCr, const __grid_constant__ CUtensorMap mCi,
             const Params p) {
    extern __shared__ uint8_t smem_raw[];
    __shared__ __align__(8) uint64_t bars[2 * STAGES];
    uint8_t* smem = smem_raw + ((1024u - (smem_u32(smem_raw) & 1023u)) & 1023u);
    const uint32_t sbase = smem_u32(smem);
    const uint32_t full0 = smem_u32(&bars[0]);
    const uint32_t empty0 = smem_u32(&bars[STAGES]);
    const int tid = threadIdx.x;
    const int wgid = tid >> 7;
    const int bid = blockIdx.x;

    if (tid == 0) {
        for (int i = 0; i < STAGES; ++i) {
            mbar_init(full0 + 8 * i, 1);
            mbar_init(empty0 + 8 * i, 16);
        }
        asm volatile("fence.mbarrier_init.release.cluster;" ::: "memory");
    }
    __syncthreads();
    cluster_sync_all();

    const int rank = bid & 1, pair = bid >> 1;
    const int g1_m = 2 * (pair >> 3) + rank, g1_n = pair & 7;
    const int part = rank;
    const int g2_m = pair >> 2, g2_n = pair & 3;
    const int grp = part * 4 + g2_n;

    if (wgid == 0) {
        if (tid == 0) {
            PipeState ps{0, 0};
            const CUtensorMap* mW = (g1_m < 8) ? &mWre : &mWim;
            gemm_produce<true>(ps, sbase, full0, empty0, mW, &mX, (g1_m & 7) * BM, g1_n * BN, 0, rank, 0, 3, 0, D_DIM / BK);
        }
        if (tid >= 32) {
#pragma unroll 1
            for (int t = tid - 32; t < 256; t += 96) { kv_prepass(p, bid * 16, t); TSTAMP2(8 + t / 96); }
            named_bar_sync(5, 96);
            TSTAMP2(11);
            if (tid == 32) asm volatile("red.release.gpu.global.add.u32 [%0], 1;" ::"l"(&g_sync[0]) : "memory");
            if (tid < 64) {
                __syncwarp();
                named_bar_sync(6, 288);
                if (tid == 32) {
                    asm volatile("fence.proxy.async;" ::: "memory");
                    asm volatile("red.release.gpu.global.add.u32 [%0], 1;" ::"l"(&g_ready[g1_m >> 1]) : "memory");
                }
             }
        }
        const CUtensorMap* mC = part ? &mCi : &mCr;
        PipeState ps2{0, 0};
        if (tid == 0) {
            counter_wait(&g_ready[grp], &g_passed[grp], 16u, 16u);
            asm volatile("fence.proxy.async;" ::: "memory");
            gemm_produce<false>(ps2, sbase, full0, empty0, mC, &mAB, g2_m * BM, grp * BN, 0, 0, 0, 0, 0, 2);
#pragma unroll 1
            for (int it = g2_n * 8; it < g2_n * 8 + 8; ++it) {
                asm volatile("cp.async.bulk.prefetch.tensor.2d.L2.global [%0, {%1, %2}];" ::"l"((uint64_t)mC),
                             "r"(it * BK), "r"(g2_m * BM) : "memory");
                asm volatile("cp.async.bulk.prefetch.tensor.2d.L2.global [%0, {%1, %2}];" ::"l"((uint64_t)mC),
                             "r"(it * BK), "r"(g2_m * BM + 64) : "memory");
            }
        }
        if (tid == 0) {
            gemm_produce<false>(ps2, sbase, full0, empty0, mC, &mAB, g2_m * BM, grp * BN, 0, 0, 0, 0, 2, S_LEN / BK);
        }
        if (tid >= 32) {
            if (tid == 32) counter_wait(&g_sync[2], &g_sync[3], 128u, 128u);
            named_bar_sync(5, 96);
#pragma unroll 1
            for (int t = tid - 32; t < 256; t += 96) out_postpass(p, bid * 16, t);
        }
        __syncwarp();
        asm volatile("barrier.cluster.arrive.release.aligned;\n barrier.cluster.wait.acquire.aligned;" ::: "memory");
        asm volatile("barrier.cluster.arrive.release.aligned;\n barrier.cluster.wait.acquire.aligned;" ::: "memory");
    } else {
        const int wg = wgid - 1;
        const int ctid = tid - 128;
        const int wtid = tid & 127;
        PipeState ps{0, 0};
        float acc[128];
        const uint32_t emptyA = 0, emptyB = mapa_u32(empty0, rank ^ 1);
        TSTAMP(0);
        gemm_consume(ps, acc, sbase, full0, empty0, emptyA, emptyB, wg, D_DIM / BK, 2);
        named_bar_sync(1, 256);
        TSTAMP(1);
        uint4 hv[8], kvr[8];
        {
            uint32_t pk[64];
#pragma unroll
            for (int i = 0; i < 64; ++i) pk[i] = pack_bf16(acc[2 * i], acc[2 * i + 1]);
            if (ctid == 0) counter_wait(&g_sync[0], &g_sync[1], 128u, 128u);
            named_bar_sync(1, 256);
            {
                const int cw = ctid >> 5, cl = ctid & 31;
                const uint4* hs = reinterpret_cast<const uint4*>(p.ssm_k + (size_t)(bid * 8 + cw) * S_LEN);
                const uint4* ks = reinterpret_cast<const uint4*>(g_kvT + (size_t)(bid * 8 + cw) * S_LEN);
#pragma unroll
                for (int it = 0; it < 8; ++it) { hv[it] = __ldg(hs + cl + 32 * it); kvr[it] = __ldcg(ks + cl + 32 * it); }
            }
            __nv_bfloat16* dst = g_abT + (size_t)(g1_m * BM + wg * 64) * 2048 + g1_n * BN;
            store_tile_bf16(pk, smem + STG1_OFF + wg * STG_WG_BYTES, dst, 2048, wtid, 3 + wg);
        }
        asm volatile("bar.arrive 6, 288;" ::: "memory");
        TSTAMP(2);
        named_bar_sync(1, 256);
        conv_phase(p, smem, bid * 8, ctid, hv, kvr);
        asm volatile("fence.proxy.async.shared::cta;" ::: "memory");
        __syncwarp();
        release_stage(empty0, emptyA, emptyB, 2);
        release_stage(empty0, emptyA, emptyB, 3);
        named_bar_sync(1, 256);
        if (ctid == 0) asm volatile("red.release.gpu.global.add.u32 [%0], 1;" ::"l"(&g_sync[2]) : "memory");
        TSTAMP(3);
#pragma unroll
        for (int i = 0; i < 128; ++i) acc[i] = 0.f;
        gemm_consume(ps, acc, sbase, full0, empty0, emptyA, emptyB, wg, S_LEN / BK, 0);
        named_bar_sync(1, 256);
        TSTAMP(4);
        asm volatile("barrier.cluster.arrive.release.aligned;\n barrier.cluster.wait.acquire.aligned;" ::: "memory");
        uint32_t pk[64];
#pragma unroll
        for (int i = 0; i < 64; ++i) pk[i] = pack_bf16(acc[2 * i], acc[2 * i + 1]);
        const uint32_t xbuf = sbase + 2 * STG_WG_BYTES + 1024;
        const bool sender = (wg != part);
        if (sender) {
            uint32_t remote;
            remote = mapa_u32(xbuf, rank ^ 1);
#pragma unroll
            for (int i = 0; i < 64; ++i) {
                asm volatile("st.shared::cluster.b32 [%0], %1;" ::"r"(remote + (uint32_t)(i * 512 + wtid * 4)), "r"(pk[i]) : "memory");
            }
        }
        asm volatile("barrier.cluster.arrive.release.aligned;\n barrier.cluster.wait.acquire.aligned;" ::: "memory");
        if (!sender) {
#pragma unroll
            for (int i = 0; i < 64; ++i) {
                uint32_t o = lds32(xbuf + (uint32_t)(i * 512 + wtid * 4));
                uint32_t re = part ? o : pk[i];
                uint32_t im = part ? pk[i] : o;
                pk[i] = pack_bf16(bf_lo(re) - bf_lo(im), bf_hi(re) - bf_hi(im));
            }
            __nv_bfloat16* dst = p.out + (size_t)(g2_m * BM + wg * 64) * 2048 + g2_n * BN;
            store_tile_bf16(pk, smem + wg * STG_WG_BYTES, dst, 2048, wtid, 3 + wg);
        }
        TSTAMP(5);
    }
}

typedef CUresult (*PFN_encodeTiled)(CUtensorMap*, CUtensorMapDataType, cuuint32_t, void*, const cuuint64_t*,
                                    const cuuint64_t*, const cuuint32_t*, const cuuint32_t*, CUtensorMapInterleave,
                                    CUtensorMapSwizzle, CUtensorMapL2promotion, CUtensorMapFloatOOBfill);

static void make_map(PFN_encodeTiled enc, CUtensorMap* m, const void* ptr, int rows, int cols, int box_rows) {
    cuuint64_t gdim[2] = {(cuuint64_t)cols, (cuuint64_t)rows};
    cuuint64_t gstr[1] = {(cuuint64_t)cols * 2};
    cuuint32_t box[2] = {64, (cuuint32_t)box_rows};
    cuuint32_t estr[2] = {1, 1};
    enc(m, CU_TENSOR_MAP_DATA_TYPE_BFLOAT16, 2, const_cast<void*>(ptr), gdim, gstr, box, estr,
        CU_TENSOR_MAP_INTERLEAVE_NONE, CU_TENSOR_MAP_SWIZZLE_128B, CU_TENSOR_MAP_L2_PROMOTION_L2_256B,
        CU_TENSOR_MAP_FLOAT_OOB_FILL_NONE);
}

extern "C" void kernel_launch(void* const* d_in, const int* in_sizes, int n_in, void* d_out, int out_size) {
    static PFN_encodeTiled enc = nullptr;
    static bool attr_set = false;
    if (!enc) {
        void* fn = nullptr;
        cudaDriverEntryPointQueryResult qres;
        cudaGetDriverEntryPoint("cuTensorMapEncodeTiled", &fn, cudaEnableDefault, &qres);
        enc = (PFN_encodeTiled)fn;
    }
    if (!attr_set) {
        cudaFuncSetAttribute(fused_kernel, cudaFuncAttributeMaxDynamicSharedMemorySize, SMEM_BYTES);
        attr_set = true;
    }
    void* abT = nullptr;
    cudaGetSymbolAddress(&abT, g_abT);

    CUtensorMap mWre, mWim, mX, mAB, mCr, mCi;
    make_map(enc, &mX, d_in[0], 2048, 1024, BN / 2);
    make_map(enc, &mCr, d_in[1], 2048, 2048, BM / 2);
    make_map(enc, &mCi, d_in[2], 2048, 2048, BM / 2);
    make_map(enc, &mWre, d_in[3], 1024, 1024, BM / 2);
    make_map(enc, &mWim, d_in[4], 1024, 1024, BM / 2);
    make_map(enc, &mAB, abT, 2048, 2048, BN / 2);

    Params p;
    p.q = (const __nv_bfloat16*)d_in[5];
    p.k = (const __nv_bfloat16*)d_in[6];
    p.v = (const __nv_bfloat16*)d_in[7];
    p.shift_k = (const __nv_bfloat16*)d_in[8];
    p.ssm_k = (const __nv_bfloat16*)d_in[9];
    p.ssm_D = (const __nv_bfloat16*)d_in[10];
    p.out = (__nv_bfloat16*)d_out;

    fused_kernel<<<128, NTHREADS, SMEM_BYTES>>>(mWre, mWim, mX, mAB, mCr, mCi, p);
}
```

```cpp
#include <cuda_runtime.h>
#include <cuda_bf16.h>
#include <cuda.h>
#include <stdint.h>

#define S_LEN 2048
#define D_DIM 1024

__device__ __nv_bfloat16 g_abT[2048 * 2048];
__device__ unsigned int g_ready[8];
__device__ unsigned int g_passed[8];
__device__ __nv_bfloat16 g_kvT[1024 * 2048];
__device__ __nv_bfloat16 g_yT[1024 * 2048];
__device__ unsigned int g_sync[4];
#define TSTAMP(i)
#define TSTAMP2(i)

__device__ __forceinline__ uint32_t smem_u32(const void* p) {
    return (uint32_t)__cvta_generic_to_shared(p);
}
__device__ __forceinline__ void mbar_init(uint32_t bar, uint32_t count) {
    asm volatile("mbarrier.init.shared::cta.b64 [%0], %1;" ::"r"(bar), "r"(count));
}
__device__ __forceinline__ void mbar_expect_tx(uint32_t bar, uint32_t bytes) {
    asm volatile("mbarrier.arrive.expect_tx.shared::cta.b64 _, [%0], %1;" ::"r"(bar), "r"(bytes) : "memory");
}
__device__ __forceinline__ void mbar_arrive(uint32_t bar) {
    asm volatile("mbarrier.arrive.shared::cta.b64 _, [%0];" ::"r"(bar) : "memory");
}
__device__ __forceinline__ void mbar_wait(uint32_t bar, uint32_t parity) {
    asm volatile(
        "{\n"
        ".reg .pred p;\n"
        "LAB_WAIT:\n"
        "mbarrier.try_wait.parity.shared::cta.b64 p, [%0], %1;\n"
        "@p bra DONE;\n"
        "bra LAB_WAIT;\n"
        "DONE:\n"
        "}\n" ::"r"(bar), "r"(parity) : "memory");
}
__device__ __forceinline__ void tma_load_2d(uint32_t dst, const CUtensorMap* map, uint32_t bar, int c0, int c1) {
    asm volatile(
        "cp.async.bulk.tensor.2d.shared::cluster.global.mbarrier::complete_tx::bytes [%0], [%1, {%3, %4}], [%2];"
        ::"r"(dst), "l"((uint64_t)map), "r"(bar), "r"(c0), "r"(c1) : "memory");
}
__device__ __forceinline__ void tma_load_2d_mc(uint32_t dst, const CUtensorMap* map, uint32_t bar, int c0, int c1,
                                               uint16_t mask) {
    asm volatile(
        "cp.async.bulk.tensor.2d.shared::cluster.global.mbarrier::complete_tx::bytes.multicast::cluster "
        "[%0], [%1, {%3, %4}], [%2], %5;"
        ::"r"(dst), "l"((uint64_t)map), "r"(bar), "r"(c0), "r"(c1), "h"(mask) : "memory");
}
__device__ __forceinline__ uint32_t mapa_u32(uint32_t addr, uint32_t rank) {
    uint32_t r;
    asm volatile("mapa.shared::cluster.u32 %0, %1, %2;" : "=r"(r) : "r"(addr), "r"(rank));
    return r;
}
__device__ __forceinline__ void mbar_arrive_cluster(uint32_t remote_bar) {
    asm volatile("mbarrier.arrive.shared::cluster.b64 _, [%0];" ::"r"(remote_bar) : "memory");
}
__device__ __forceinline__ void cluster_sync_all() {
    asm volatile("barrier.cluster.arrive.release.aligned;\n barrier.cluster.wait.acquire.aligned;" ::: "memory");
}
__device__ __forceinline__ void wgmma_fence() { asm volatile("wgmma.fence.sync.aligned;" ::: "memory"); }
__device__ __forceinline__ void wgmma_commit() { asm volatile("wgmma.commit_group.sync.aligned;" ::: "memory"); }
template <int N>
__device__ __forceinline__ void wgmma_wait() { asm volatile("wgmma.wait_group.sync.aligned %0;" ::"n"(N) : "memory"); }

__device__ __forceinline__ uint64_t make_desc_sw128(uint32_t saddr) {
    uint64_t d = 0;
    d |= (uint64_t)((saddr & 0x3FFFF) >> 4);
    d |= (uint64_t)1 << 16;
    d |= (uint64_t)64 << 32;
    d |= (uint64_t)1 << 62;
    return d;
}

#define ACC8(a, i) "+f"(a[i]), "+f"(a[i + 1]), "+f"(a[i + 2]), "+f"(a[i + 3]), "+f"(a[i + 4]), "+f"(a[i + 5]), "+f"(a[i + 6]), "+f"(a[i + 7])

__device__ __forceinline__ void wgmma_m64n256k16(float (&d)[128], uint64_t da, uint64_t db, int scale_d) {
    asm volatile(
        "{\n"
        ".reg .pred p;\n"
        "setp.ne.b32 p, %130, 0;\n"
        "wgmma.mma_async.sync.aligned.m64n256k16.f32.bf16.bf16 "
        "{%0, %1, %2, %3, %4, %5, %6, %7, %8, %9, %10, %11, %12, %13, %14, %15, "
        "%16, %17, %18, %19, %20, %21, %22, %23, %24, %25, %26, %27, %28, %29, %30, %31, "
        "%32, %33, %34, %35, %36, %37, %38, %39, %40, %41, %42, %43, %44, %45, %46, %47, "
        "%48, %49, %50, %51, %52, %53, %54, %55, %56, %57, %58, %59, %60, %61, %62, %63, "
        "%64, %65, %66, %67, %68, %69, %70, %71, %72, %73, %74, %75, %76, %77, %78, %79, "
        "%80, %81, %82, %83, %84, %85, %86, %87, %88, %89, %90, %91, %92, %93, %94, %95, "
        "%96, %97, %98, %99, %100, %101, %102, %103, %104, %105, %106, %107, %108, %109, %110, %111, "
        "%112, %113, %114, %115, %116, %117, %118, %119, %120, %121, %122, %123, %124, %125, %126, %127}, "
        "%128, %129, p, 1, 1, 0, 0;\n"
        "}\n"
        : ACC8(d, 0), ACC8(d, 8), ACC8(d, 16), ACC8(d, 24), ACC8(d, 32), ACC8(d, 40), ACC8(d, 48), ACC8(d, 56),
          ACC8(d, 64), ACC8(d, 72), ACC8(d, 80), ACC8(d, 88), ACC8(d, 96), ACC8(d, 104), ACC8(d, 112), ACC8(d, 120)
        : "l"(da), "l"(db), "r"(scale_d));
}

__device__ __forceinline__ void wgmma_rs_n128(float (&d)[64], uint32_t a0, uint32_t a1, uint32_t a2, uint32_t a3,
                                              uint64_t db) {
    asm volatile(
        "wgmma.mma_async.sync.aligned.m64n128k16.f32.bf16.bf16 {%0, %1, %2, %3, %4, %5, %6, %7, %8, %9, %10, %11, %12, %13, %14, %15, %16, %17, %18, %19, %20, %21, %22, %23, %24, %25, %26, %27, %28, %29, %30, %31, %32, %33, %34, %35, %36, %37, %38, %39, %40, %41, %42, %43, %44, %45, %46, %47, %48, %49, %50, %51, %52, %53, %54, %55, %56, %57, %58, %59, %60, %61, %62, %63}, {%64, %65, %66, %67}, %68, 1, 1, 1, 0;\n"
        : "+f"(d[0]), "+f"(d[1]), "+f"(d[2]), "+f"(d[3]), "+f"(d[4]), "+f"(d[5]), "+f"(d[6]), "+f"(d[7]), "+f"(d[8]), "+f"(d[9]), "+f"(d[10]), "+f"(d[11]), "+f"(d[12]), "+f"(d[13]), "+f"(d[14]), "+f"(d[15]), "+f"(d[16]), "+f"(d[17]), "+f"(d[18]), "+f"(d[19]), "+f"(d[20]), "+f"(d[21]), "+f"(d[22]), "+f"(d[23]), "+f"(d[24]), "+f"(d[25]), "+f"(d[26]), "+f"(d[27]), "+f"(d[28]), "+f"(d[29]), "+f"(d[30]), "+f"(d[31]), "+f"(d[32]), "+f"(d[33]), "+f"(d[34]), "+f"(d[35]), "+f"(d[36]), "+f"(d[37]), "+f"(d[38]), "+f"(d[39]), "+f"(d[40]), "+f"(d[41]), "+f"(d[42]), "+f"(d[43]), "+f"(d[44]), "+f"(d[45]), "+f"(d[46]), "+f"(d[47]), "+f"(d[48]), "+f"(d[49]), "+f"(d[50]), "+f"(d[51]), "+f"(d[52]), "+f"(d[53]), "+f"(d[54]), "+f"(d[55]), "+f"(d[56]), "+f"(d[57]), "+f"(d[58]), "+f"(d[59]), "+f"(d[60]), "+f"(d[61]), "+f"(d[62]), "+f"(d[63])
        : "r"(a0), "r"(a1), "r"(a2), "r"(a3), "l"(db));
}
__device__ __forceinline__ void wgmma_rs_n96(float (&d)[64], uint32_t a0, uint32_t a1, uint32_t a2, uint32_t a3,
                                              uint64_t db) {
    asm volatile(
        "wgmma.mma_async.sync.aligned.m64n96k16.f32.bf16.bf16 {%0, %1, %2, %3, %4, %5, %6, %7, %8, %9, %10, %11, %12, %13, %14, %15, %16, %17, %18, %19, %20, %21, %22, %23, %24, %25, %26, %27, %28, %29, %30, %31, %32, %33, %34, %35, %36, %37, %38, %39, %40, %41, %42, %43, %44, %45, %46, %47}, {%48, %49, %50, %51}, %52, 1, 1, 1, 0;\n"
        : "+f"(d[16]), "+f"(d[17]), "+f"(d[18]), "+f"(d[19]), "+f"(d[20]), "+f"(d[21]), "+f"(d[22]), "+f"(d[23]), "+f"(d[24]), "+f"(d[25]), "+f"(d[26]), "+f"(d[27]), "+f"(d[28]), "+f"(d[29]), "+f"(d[30]), "+f"(d[31]), "+f"(d[32]), "+f"(d[33]), "+f"(d[34]), "+f"(d[35]), "+f"(d[36]), "+f"(d[37]), "+f"(d[38]), "+f"(d[39]), "+f"(d[40]), "+f"(d[41]), "+f"(d[42]), "+f"(d[43]), "+f"(d[44]), "+f"(d[45]), "+f"(d[46]), "+f"(d[47]), "+f"(d[48]), "+f"(d[49]), "+f"(d[50]), "+f"(d[51]), "+f"(d[52]), "+f"(d[53]), "+f"(d[54]), "+f"(d[55]), "+f"(d[56]), "+f"(d[57]), "+f"(d[58]), "+f"(d[59]), "+f"(d[60]), "+f"(d[61]), "+f"(d[62]), "+f"(d[63])
        : "r"(a0), "r"(a1), "r"(a2), "r"(a3), "l"(db));
}
__device__ __forceinline__ void wgmma_rs_n64(float (&d)[64], uint32_t a0, uint32_t a1, uint32_t a2, uint32_t a3,
                                              uint64_t db) {
    asm volatile(
        "wgmma.mma_async.sync.aligned.m64n64k16.f32.bf16.bf16 {%0, %1, %2, %3, %4, %5, %6, %7, %8, %9, %10, %11, %12, %13, %14, %15, %16, %17, %18, %19, %20, %21, %22, %23, %24, %25, %26, %27, %28, %29, %30, %31}, {%32, %33, %34, %35}, %36, 1, 1, 1, 0;\n"
        : "+f"(d[32]), "+f"(d[33]), "+f"(d[34]), "+f"(d[35]), "+f"(d[36]), "+f"(d[37]), "+f"(d[38]), "+f"(d[39]), "+f"(d[40]), "+f"(d[41]), "+f"(d[42]), "+f"(d[43]), "+f"(d[44]), "+f"(d[45]), "+f"(d[46]), "+f"(d[47]), "+f"(d[48]), "+f"(d[49]), "+f"(d[50]), "+f"(d[51]), "+f"(d[52]), "+f"(d[53]), "+f"(d[54]), "+f"(d[55]), "+f"(d[56]), "+f"(d[57]), "+f"(d[58]), "+f"(d[59]), "+f"(d[60]), "+f"(d[61]), "+f"(d[62]), "+f"(d[63])
        : "r"(a0), "r"(a1), "r"(a2), "r"(a3), "l"(db));
}
__device__ __forceinline__ void wgmma_rs_n32(float (&d)[64], uint32_t a0, uint32_t a1, uint32_t a2, uint32_t a3,
                                              uint64_t db) {
    asm volatile(
        "wgmma.mma_async.sync.aligned.m64n32k16.f32.bf16.bf16 {%0, %1, %2, %3, %4, %5, %6, %7, %8, %9, %10, %11, %12, %13, %14, %15}, {%16, %17, %18, %19}, %20, 1, 1, 1, 0;\n"
        : "+f"(d[48]), "+f"(d[49]), "+f"(d[50]), "+f"(d[51]), "+f"(d[52]), "+f"(d[53]), "+f"(d[54]), "+f"(d[55]), "+f"(d[56]), "+f"(d[57]), "+f"(d[58]), "+f"(d[59]), "+f"(d[60]), "+f"(d[61]), "+f"(d[62]), "+f"(d[63])
        : "r"(a0), "r"(a1), "r"(a2), "r"(a3), "l"(db));
}

__device__ __forceinline__ void mma_bf16_16816(float (&c)[4], uint32_t a0, uint32_t a1, uint32_t a2, uint32_t a3,
                                               uint32_t b0, uint32_t b1) {
    asm volatile(
        "mma.sync.aligned.m16n8k16.row.col.f32.bf16.bf16.f32 {%0,%1,%2,%3}, {%4,%5,%6,%7}, {%8,%9}, {%0,%1,%2,%3};"
        : "+f"(c[0]), "+f"(c[1]), "+f"(c[2]), "+f"(c[3])
        : "r"(a0), "r"(a1), "r"(a2), "r"(a3), "r"(b0), "r"(b1));
}

__device__ __forceinline__ uint32_t lds32(uint32_t addr) {
    uint32_t v;
    asm volatile("ld.shared.b32 %0, [%1];" : "=r"(v) : "r"(addr));
    return v;
}
__device__ __forceinline__ uint32_t pack_bf16(float lo, float hi) {
    __nv_bfloat162 t = __floats2bfloat162_rn(lo, hi);
    return *reinterpret_cast<uint32_t*>(&t);
}
__device__ __forceinline__ float bf_lo(uint32_t v) { return __uint_as_float(v << 16); }
__device__ __forceinline__ float bf_hi(uint32_t v) { return __uint_as_float(v & 0xffff0000u); }
__device__ __forceinline__ __nv_bfloat162 u2b(uint32_t v) { return *reinterpret_cast<__nv_bfloat162*>(&v); }
__device__ __forceinline__ uint32_t b2u(__nv_bfloat162 v) { return *reinterpret_cast<uint32_t*>(&v); }
__device__ __forceinline__ float rbf(float x) { return __bfloat162float(__float2bfloat16_rn(x)); }

__device__ __forceinline__ void named_bar_sync(int id, int n) {
    asm volatile("bar.sync %0, %1;" ::"r"(id), "r"(n) : "memory");
}

constexpr int BM = 128, BN = 256, BK = 64, STAGES = 4;
constexpr int A_BYTES = BM * BK * 2;
constexpr int B_BYTES = BN * BK * 2;
constexpr int STAGE_BYTES = A_BYTES + B_BYTES;
constexpr int SMEM_BYTES = STAGES * STAGE_BYTES + 34688 + 1024;
constexpr int NTHREADS = 384;

constexpr int STG_PITCH = 528;
constexpr int STG_WG_BYTES = 64 * STG_PITCH;

constexpr int KV_PITCH = 112 + 2048 + 8;
constexpr int KV_BYTES = 8 * KV_PITCH * 2;
constexpr int REV_PITCH = 2096;
constexpr int REV_BYTES = 8 * 2 * REV_PITCH * 2;
constexpr int YS_BYTES = 2048 * 8 * 2;
constexpr int CONV_KV_OFF = STAGES * STAGE_BYTES;
constexpr int CONV_REV_OFF = 2 * STAGE_BYTES;
constexpr int STG1_OFF = 2 * STAGE_BYTES;
constexpr int CONV_YS_OFF = CONV_REV_OFF + REV_BYTES;
static_assert(CONV_REV_OFF + REV_BYTES <= STAGES * STAGE_BYTES && STG1_OFF + 2 * STG_WG_BYTES <= STAGES * STAGE_BYTES && KV_BYTES <= 34688, "conv smem");
constexpr int PL_PAD = 32;
constexpr int PLANE_BYTES = (PL_PAD + 128) * 16;
constexpr int KVP_BYTES = 2 * PLANE_BYTES;
constexpr int KVP_OFF_HI = CONV_REV_OFF + REV_BYTES;
static_assert(6 * KVP_BYTES <= 34688 && KVP_OFF_HI + 2 * KVP_BYTES <= STAGES * STAGE_BYTES, "kv planes");
constexpr int YP = 131;
static_assert(16 * YP * 4 <= 2 * REV_PITCH * 2, "Y buffer");
constexpr int REV_Y0 = 2054;

struct Params {
    const __nv_bfloat16 *q, *k, *v, *shift_k, *ssm_k, *ssm_D;
    __nv_bfloat16* out;
};

struct PipeState {
    int stage;
    uint32_t phase;
    __device__ __forceinline__ void advance() {
        if (++stage == STAGES) { stage = 0; phase ^= 1; }
    }
};

template <bool B_MC>
__device__ __forceinline__ void gemm_produce(PipeState& ps, uint32_t sbase, uint32_t full0, uint32_t empty0,
                                             const CUtensorMap* mA, const CUtensorMap* mB, int arow, int brow,
                                             int ahalf, int bhalf, uint16_t maskA, uint16_t maskB, int k0, int nk) {
#pragma unroll 1
    for (int it = k0; it < nk; ++it) {
        mbar_wait(empty0 + 8 * ps.stage, ps.phase ^ 1);
        uint32_t fb = full0 + 8 * ps.stage;
        mbar_expect_tx(fb, STAGE_BYTES);
        uint32_t sa = sbase + ps.stage * STAGE_BYTES;
        tma_load_2d(sa, mA, fb, it * BK, arow);
        tma_load_2d(sa + A_BYTES / 2, mA, fb, it * BK, arow + BM / 2);
        if (B_MC) {
            tma_load_2d_mc(sa + A_BYTES + bhalf * (B_BYTES / 2), mB, fb, it * BK, brow + bhalf * (BN / 2), maskB);
        } else {
            tma_load_2d(sa + A_BYTES, mB, fb, it * BK, brow);
            tma_load_2d(sa + A_BYTES + B_BYTES / 2, mB, fb, it * BK, brow + BN / 2);
        }
        ps.advance();
    }
}

__device__ __forceinline__ void release_stage(uint32_t empty0, uint32_t emptyA, uint32_t emptyB, int stage) {
    if ((threadIdx.x & 31) == 0) {
        mbar_arrive(empty0 + 8 * stage);
        mbar_arrive_cluster(emptyB + 8 * stage);
    }
}

__device__ __forceinline__ void gemm_consume(PipeState& ps, float (&acc)[128], uint32_t sbase, uint32_t full0,
                                             uint32_t empty0, uint32_t emptyA, uint32_t emptyB, int wg, int nk,
                                             int n_hold) {
    int prev_stage = -1;
#pragma unroll 1
    for (int it = 0; it < nk; ++it) {
        mbar_wait(full0 + 8 * ps.stage, ps.phase);
        uint32_t sa = sbase + ps.stage * STAGE_BYTES + wg * (64 * 128);
        uint32_t sb = sbase + ps.stage * STAGE_BYTES + A_BYTES;
        uint64_t da = make_desc_sw128(sa);
        uint64_t db = make_desc_sw128(sb);
        wgmma_fence();
#pragma unroll
        for (int kk = 0; kk < 4; ++kk) {
            wgmma_m64n256k16(acc, da + (uint64_t)(kk * 2), db + (uint64_t)(kk * 2), (it > 0 || kk > 0) ? 1 : 0);
        }
        wgmma_commit();
        if (prev_stage >= 0) {
            wgmma_wait<1>();
            if (it - 1 < nk - n_hold) release_stage(empty0, emptyA, emptyB, prev_stage);
        }
        prev_stage = ps.stage;
        ps.advance();
    }
    wgmma_wait<0>();
    if (n_hold == 0) release_stage(empty0, emptyA, emptyB, prev_stage);
}

__device__ __forceinline__ void store_tile_bf16(const uint32_t (&pk)[64], uint8_t* stg, __nv_bfloat16* gdst, int ld,
                                                int wg_tid, int bar_id) {
    const int warp = wg_tid >> 5, lane = wg_tid & 31;
    const int r0 = warp * 16 + (lane >> 2);
    const int c0 = (lane & 3) * 2;
#pragma unroll
    for (int j = 0; j < 32; ++j) {
        *reinterpret_cast<uint32_t*>(stg + r0 * STG_PITCH + (j * 8 + c0) * 2) = pk[2 * j];
        *reinterpret_cast<uint32_t*>(stg + (r0 + 8) * STG_PITCH + (j * 8 + c0) * 2) = pk[2 * j + 1];
    }
    named_bar_sync(bar_id, 128);
#pragma unroll
    for (int p = 0; p < 16; ++p) {
        int r = p * 4 + (wg_tid >> 5);
        int cb = (wg_tid & 31) * 16;
        uint4 val = *reinterpret_cast<const uint4*>(stg + r * STG_PITCH + cb);
        *reinterpret_cast<uint4*>(reinterpret_cast<uint8_t*>(gdst + (size_t)r * ld) + cb) = val;
    }
}

__device__ __forceinline__ void counter_wait(unsigned int* ready, unsigned int* passed, unsigned int n_ready,
                                             unsigned int n_wait) {
    unsigned int v;
    long long spins = 0;
    do {
        asm volatile("ld.acquire.gpu.global.u32 %0, [%1];" : "=r"(v) : "l"(ready) : "memory");
    } while (v < n_ready && ++spins < (1ll << 26));
    unsigned int old = atomicAdd(passed, 1u);
    if (old == n_wait - 1) {
        *passed = 0;
        *ready = 0;
        __threadfence();
    }
}

__device__ __forceinline__ void kv_prepass(const Params& p, int s0, int ctid) {
    const int c0 = ctid * 4;
    uint2 kr[19], vr[16];
#pragma unroll
    for (int j = 0; j < 19; ++j) {
        int s = s0 - 3 + j;
        if (s >= 0) kr[j] = __ldg(reinterpret_cast<const uint2*>(p.k + (size_t)s * D_DIM + c0));
        else kr[j] = make_uint2(0, 0);
    }
#pragma unroll
    for (int j = 0; j < 16; ++j) vr[j] = __ldg(reinterpret_cast<const uint2*>(p.v + (size_t)(s0 + j) * D_DIM + c0));
    uint4 w0 = __ldg(reinterpret_cast<const uint4*>(p.shift_k + (size_t)c0 * 4));
    uint4 w1 = __ldg(reinterpret_cast<const uint4*>(p.shift_k + (size_t)c0 * 4 + 8));
    uint32_t wt[2][4];
    wt[0][0] = __byte_perm(w0.x, w0.z, 0x5410); wt[0][1] = __byte_perm(w0.x, w0.z, 0x7632);
    wt[0][2] = __byte_perm(w0.y, w0.w, 0x5410); wt[0][3] = __byte_perm(w0.y, w0.w, 0x7632);
    wt[1][0] = __byte_perm(w1.x, w1.z, 0x5410); wt[1][1] = __byte_perm(w1.x, w1.z, 0x7632);
    wt[1][2] = __byte_perm(w1.y, w1.w, 0x5410); wt[1][3] = __byte_perm(w1.y, w1.w, 0x7632);
#pragma unroll
    for (int pr = 0; pr < 2; ++pr) {
        uint32_t r[16];
#pragma unroll
        for (int j = 0; j < 16; ++j) {
            __nv_bfloat162 k0 = u2b(pr ? kr[j].y : kr[j].x), k1 = u2b(pr ? kr[j + 1].y : kr[j + 1].x);
            __nv_bfloat162 k2 = u2b(pr ? kr[j + 2].y : kr[j + 2].x), k3 = u2b(pr ? kr[j + 3].y : kr[j + 3].x);
            __nv_bfloat162 acc = __hmul2(k0, u2b(wt[pr][3]));
            acc = __hadd2(acc, __hmul2(k1, u2b(wt[pr][2])));
            acc = __hadd2(acc, __hmul2(k2, u2b(wt[pr][1])));
            acc = __hadd2(acc, __hmul2(k3, u2b(wt[pr][0])));
            acc = __hmul2(acc, u2b(pr ? vr[j].y : vr[j].x));
            r[j] = b2u(acc);
        }
        uint32_t lo[8], hi[8];
#pragma unroll
        for (int j = 0; j < 8; ++j) {
            lo[j] = __byte_perm(r[2 * j], r[2 * j + 1], 0x5410);
            hi[j] = __byte_perm(r[2 * j], r[2 * j + 1], 0x7632);
        }
        uint4* d0 = reinterpret_cast<uint4*>(g_kvT + (size_t)(c0 + 2 * pr) * S_LEN + s0);
        uint4* d1 = reinterpret_cast<uint4*>(g_kvT + (size_t)(c0 + 2 * pr + 1) * S_LEN + s0);
        d0[0] = make_uint4(lo[0], lo[1], lo[2], lo[3]);
        d0[1] = make_uint4(lo[4], lo[5], lo[6], lo[7]);
        d1[0] = make_uint4(hi[0], hi[1], hi[2], hi[3]);
        d1[1] = make_uint4(hi[4], hi[5], hi[6], hi[7]);
    }
}

__device__ __forceinline__ void out_postpass(const Params& p, int s0, int ctid) {
    const int c0 = ctid * 4;
    uint2 qr[16];
#pragma unroll
    for (int j = 0; j < 16; ++j) qr[j] = __ldg(reinterpret_cast<const uint2*>(p.q + (size_t)(s0 + j) * D_DIM + c0));
    uint4 yy[4][2];
#pragma unroll
    for (int c = 0; c < 4; ++c) {
        const uint4* src = reinterpret_cast<const uint4*>(g_yT + (size_t)(c0 + c) * S_LEN + s0);
        yy[c][0] = __ldcg(src);
        yy[c][1] = __ldcg(src + 1);
    }
#pragma unroll
    for (int j = 0; j < 16; j += 2) {
        uint32_t y0 = reinterpret_cast<const uint32_t*>(&yy[0][0])[j >> 1], y1 = reinterpret_cast<const uint32_t*>(&yy[1][0])[j >> 1];
        uint32_t y2 = reinterpret_cast<const uint32_t*>(&yy[2][0])[j >> 1], y3 = reinterpret_cast<const uint32_t*>(&yy[3][0])[j >> 1];
        uint2 o;
        o.x = b2u(__hmul2(u2b(qr[j].x), u2b(__byte_perm(y0, y1, 0x5410))));
        o.y = b2u(__hmul2(u2b(qr[j].y), u2b(__byte_perm(y2, y3, 0x5410))));
        *reinterpret_cast<uint2*>(p.out + (size_t)(s0 + j) * 2048 + 1024 + c0) = o;
        o.x = b2u(__hmul2(u2b(qr[j + 1].x), u2b(__byte_perm(y0, y1, 0x7632))));
        o.y = b2u(__hmul2(u2b(qr[j + 1].y), u2b(__byte_perm(y2, y3, 0x7632))));
        *reinterpret_cast<uint2*>(p.out + (size_t)(s0 + j + 1) * 2048 + 1024 + c0) = o;
    }
}

__device__ __forceinline__ void conv_phase(const Params& p, uint8_t* smem, int ch0, int ctid, const uint4 (&hv)[8], const uint4 (&t)[8]) {
    const int warp = ctid >> 5, lane = ctid & 31;
    __nv_bfloat16* kvs = reinterpret_cast<__nv_bfloat16*>(smem + CONV_KV_OFF) + (size_t)warp * KV_PITCH;
    __nv_bfloat16* rev = reinterpret_cast<__nv_bfloat16*>(smem + CONV_REV_OFF);

    {
        __nv_bfloat16* r0 = rev + (size_t)(warp * 2) * REV_PITCH;
        __nv_bfloat16* r1 = r0 + REV_PITCH;
        const unsigned short* hraw = reinterpret_cast<const unsigned short*>(p.ssm_k + (size_t)(ch0 + warp) * S_LEN);
#pragma unroll
        for (int it = 0; it < 8; ++it) {
            int idx = 8 * (lane + 32 * it);
            uint32_t prev = (idx > 0) ? (uint32_t)__ldg(hraw + idx - 1) : 0u;
            uint4 h4 = hv[it];
            uint4 o1, o0;
            o1.x = __byte_perm(h4.w, 0, 0x1032); o1.y = __byte_perm(h4.z, 0, 0x1032);
            o1.z = __byte_perm(h4.y, 0, 0x1032); o1.w = __byte_perm(h4.x, 0, 0x1032);
            *reinterpret_cast<uint4*>(r1 + (REV_Y0 - 6 - idx)) = o1;
            o0.x = __byte_perm(h4.w, h4.z, 0x7610);
            o0.y = __byte_perm(h4.z, h4.y, 0x7610);
            o0.z = __byte_perm(h4.y, h4.x, 0x7610);
            o0.w = __byte_perm(h4.x, prev, 0x5410);
            *reinterpret_cast<uint4*>(r0 + (REV_Y0 - 6 - idx)) = o0;
        }
        if (lane == 31) r0[REV_Y0 - 2047] = reinterpret_cast<const __nv_bfloat16*>(&hv[7])[7];
        if (lane < 24) {
            int idx = -1 - lane;
            r0[REV_Y0 - idx] = __float2bfloat16_rn(0.f);
            r1[REV_Y0 + 1 - idx] = __float2bfloat16_rn(0.f);
        }
    }
    {
        uint8_t* kp = smem + ((warp < 6) ? (CONV_KV_OFF + warp * KVP_BYTES) : (KVP_OFF_HI + (warp - 6) * KVP_BYTES));
#pragma unroll
        for (int it = 0; it < 8; ++it) {
            int c = lane + 32 * it;
            *reinterpret_cast<uint4*>(kp + (c & 1) * PLANE_BYTES + (PL_PAD + (c >> 1)) * 16) = t[it];
        }
        *reinterpret_cast<uint4*>(kp + lane * 16) = make_uint4(0, 0, 0, 0);
        *reinterpret_cast<uint4*>(kp + PLANE_BYTES + lane * 16) = make_uint4(0, 0, 0, 0);
    }
    asm volatile("fence.proxy.async.shared::cta;" ::: "memory");
    const int wg = ctid >> 7, w4 = warp & 3, wtid = ctid & 127;
    named_bar_sync(3 + wg, 128);
    TSTAMP(6);
    const int g = lane >> 2, c2 = (lane & 3) * 2;
#pragma unroll 1
    for (int cc = 0; cc < 4; ++cc) {
        const int ch = wg * 4 + cc;
        const uint32_t kp = smem_u32(smem) + (uint32_t)((ch < 6) ? (CONV_KV_OFF + ch * KVP_BYTES) : (KVP_OFF_HI + (ch - 6) * KVP_BYTES));
        const uint32_t rev_base = smem_u32(rev + (size_t)(ch * 2 + (g & 1)) * REV_PITCH) +
                                  2u * (uint32_t)(REV_Y0 + (g & 1) - g + c2 - 16 * w4);
        float acc[64];
#pragma unroll
        for (int i = 0; i < 64; ++i) acc[i] = 0.f;
        const uint64_t dbase = ((uint64_t)(PLANE_BYTES >> 4) << 16) | ((uint64_t)(128 >> 4) << 32);
#pragma unroll
        for (int qd = 0; qd < 4; ++qd) {
            uint32_t f[8][3];
#pragma unroll
            for (int st = 0; st < 8; ++st) {
                int delta = 16 * (32 * qd + 4 * st);
                f[st][0] = lds32(rev_base - 2u * (uint32_t)(delta - 8));
                f[st][1] = lds32(rev_base - 2u * (uint32_t)(delta));
                f[st][2] = lds32(rev_base - 2u * (uint32_t)(delta + 8));
            }
            wgmma_fence();
#pragma unroll
            for (int st = 0; st < 8; ++st) {
                uint32_t baddr = kp + (uint32_t)((PL_PAD - 4 * st) * 16);
                uint64_t db = dbase | (uint64_t)((baddr & 0x3FFFF) >> 4);
                if (qd == 0) wgmma_rs_n128(acc, f[st][1], f[st][2], f[st][0], f[st][1], db);
                else if (qd == 1) wgmma_rs_n96(acc, f[st][1], f[st][2], f[st][0], f[st][1], db);
                else if (qd == 2) wgmma_rs_n64(acc, f[st][1], f[st][2], f[st][0], f[st][1], db);
                else wgmma_rs_n32(acc, f[st][1], f[st][2], f[st][0], f[st][1], db);
            }
            wgmma_commit();
            wgmma_wait<0>();
        }
        named_bar_sync(3 + wg, 128);
        float* Y = reinterpret_cast<float*>(rev + (size_t)(ch * 2) * REV_PITCH);
#pragma unroll 1
        for (int r = 0; r < 4; ++r) {
            if (w4 == r) {
#pragma unroll
                for (int j = 0; j < 16; ++j) {
#pragma unroll
                    for (int e = 0; e < 4; ++e) {
                        int col = 8 * j + c2 + (e & 1) + r;
                        int row = g + 8 * (e >> 1);
                        if (col < 128) {
                            if (r == 0) Y[row * YP + col] = acc[4 * j + e];
                            else Y[row * YP + col] += acc[4 * j + e];
                        }
                    }
                }
            }
            named_bar_sync(3 + wg, 128);
        }
        {
            const __nv_bfloat162 D2 = __bfloat162bfloat162(p.ssm_D[ch0 + ch]);
#pragma unroll
            for (int it = 0; it < 2; ++it) {
                int c = wtid + 128 * it;
                int n = c >> 1, hh = c & 1;
                uint4 kv4;
                asm volatile("ld.shared.v4.b32 {%0,%1,%2,%3}, [%4];" : "=r"(kv4.x), "=r"(kv4.y), "=r"(kv4.z), "=r"(kv4.w)
                             : "r"(kp + (uint32_t)(hh * PLANE_BYTES + (PL_PAD + n) * 16)));
                const uint32_t* kvw = reinterpret_cast<const uint32_t*>(&kv4);
                uint32_t o[4];
#pragma unroll
                for (int e = 0; e < 4; ++e) {
                    float y0 = Y[(8 * hh + 2 * e) * YP + n], y1 = Y[(8 * hh + 2 * e + 1) * YP + n];
                    __nv_bfloat162 yb = __floats2bfloat162_rn(y0, y1);
                    o[e] = b2u(__hadd2(yb, __hmul2(u2b(kvw[e]), D2)));
                }
                *reinterpret_cast<uint4*>(g_yT + (size_t)(ch0 + ch) * S_LEN + 8 * c) = make_uint4(o[0], o[1], o[2], o[3]);
            }
        }
    }
    TSTAMP(7);
}

__global__ void __cluster_dims__(2, 1, 1) __launch_bounds__(NTHREADS, 1)
fused_kernel(const __grid_constant__ CUtensorMap mWre, const __grid_constant__ CUtensorMap mWim,
             const __grid_constant__ CUtensorMap mX, const __grid_constant__ CUtensorMap mAB,
             const __grid_constant__ CUtensorMap mCr, const __grid_constant__ CUtensorMap mCi,
             const Params p) {
    extern __shared__ uint8_t smem_raw[];
    __shared__ __align__(8) uint64_t bars[2 * STAGES];
    uint8_t* smem = smem_raw + ((1024u - (smem_u32(smem_raw) & 1023u)) & 1023u);
    const uint32_t sbase = smem_u32(smem);
    const uint32_t full0 = smem_u32(&bars[0]);
    const uint32_t empty0 = smem_u32(&bars[STAGES]);
    const int tid = threadIdx.x;
    const int wgid = tid >> 7;
    const int bid = blockIdx.x;

    if (tid == 0) {
        for (int i = 0; i < STAGES; ++i) {
            mbar_init(full0 + 8 * i, 1);
            mbar_init(empty0 + 8 * i, 16);
        }
        asm volatile("fence.mbarrier_init.release.cluster;" ::: "memory");
    }
    __syncthreads();
    cluster_sync_all();

    const int rank = bid & 1, pair = bid >> 1;
    const int g1_m = 2 * (pair >> 3) + rank, g1_n = pair & 7;
    const int part = rank;
    const int g2_m = pair >> 2, g2_n = pair & 3;
    const int grp = part * 4 + g2_n;

    if (wgid == 0) {
        if (tid == 0) {
            PipeState ps{0, 0};
            const CUtensorMap* mW = (g1_m < 8) ? &mWre : &mWim;
            gemm_produce<true>(ps, sbase, full0, empty0, mW, &mX, (g1_m & 7) * BM, g1_n * BN, 0, rank, 0, 3, 0, D_DIM / BK);
        }
        if (tid >= 32) {
#pragma unroll 1
            for (int t = tid - 32; t < 256; t += 96) { kv_prepass(p, bid * 16, t); TSTAMP2(8 + t / 96); }
            named_bar_sync(5, 96);
            TSTAMP2(11);
            if (tid == 32) asm volatile("red.release.gpu.global.add.u32 [%0], 1;" ::"l"(&g_sync[0]) : "memory");
            if (tid < 64) {
                __syncwarp();
                named_bar_sync(6, 288);
                if (tid == 32) {
                    asm volatile("fence.proxy.async;" ::: "memory");
                    asm volatile("red.release.gpu.global.add.u32 [%0], 1;" ::"l"(&g_ready[g1_m >> 1]) : "memory");
                }
             }
        }
        const CUtensorMap* mC = part ? &mCi : &mCr;
        PipeState ps2{0, 0};
        if (tid == 0) {
            counter_wait(&g_ready[grp], &g_passed[grp], 16u, 16u);
            asm volatile("fence.proxy.async;" ::: "memory");
            gemm_produce<false>(ps2, sbase, full0, empty0, mC, &mAB, g2_m * BM, grp * BN, 0, 0, 0, 0, 0, 2);
#pragma unroll 1
            for (int it = g2_n * 8; it < g2_n * 8 + 8; ++it) {
                asm volatile("cp.async.bulk.prefetch.tensor.2d.L2.global [%0, {%1, %2}];" ::"l"((uint64_t)mC),
                             "r"(it * BK), "r"(g2_m * BM) : "memory");
                asm volatile("cp.async.bulk.prefetch.tensor.2d.L2.global [%0, {%1, %2}];" ::"l"((uint64_t)mC),
                             "r"(it * BK), "r"(g2_m * BM + 64) : "memory");
            }
        }
        if (tid == 0) {
            gemm_produce<false>(ps2, sbase, full0, empty0, mC, &mAB, g2_m * BM, grp * BN, 0, 0, 0, 0, 2, S_LEN / BK);
        }
        if (tid >= 32) {
            if (tid == 32) counter_wait(&g_sync[2], &g_sync[3], 128u, 128u);
            named_bar_sync(5, 96);
#pragma unroll 1
            for (int t = tid - 32; t < 256; t += 96) out_postpass(p, bid * 16, t);
        }
        __syncwarp();
        asm volatile("barrier.cluster.arrive.release.aligned;\n barrier.cluster.wait.acquire.aligned;" ::: "memory");
        asm volatile("barrier.cluster.arrive.release.aligned;\n barrier.cluster.wait.acquire.aligned;" ::: "memory");
    } else {
        const int wg = wgid - 1;
        const int ctid = tid - 128;
        const int wtid = tid & 127;
        PipeState ps{0, 0};
        float acc[128];
        const uint32_t emptyA = 0, emptyB = mapa_u32(empty0, rank ^ 1);
        TSTAMP(0);
        gemm_consume(ps, acc, sbase, full0, empty0, emptyA, emptyB, wg, D_DIM / BK, 2);
        named_bar_sync(1, 256);
        TSTAMP(1);
        uint4 hv[8], kvr[8];
        {
            uint32_t pk[64];
#pragma unroll
            for (int i = 0; i < 64; ++i) pk[i] = pack_bf16(acc[2 * i], acc[2 * i + 1]);
            if (ctid == 0) counter_wait(&g_sync[0], &g_sync[1], 128u, 128u);
            named_bar_sync(1, 256);
            {
                const int cw = ctid >> 5, cl = ctid & 31;
                const uint4* hs = reinterpret_cast<const uint4*>(p.ssm_k + (size_t)(bid * 8 + cw) * S_LEN);
                const uint4* ks = reinterpret_cast<const uint4*>(g_kvT + (size_t)(bid * 8 + cw) * S_LEN);
#pragma unroll
                for (int it = 0; it < 8; ++it) { hv[it] = __ldg(hs + cl + 32 * it); kvr[it] = __ldcg(ks + cl + 32 * it); }
            }
            __nv_bfloat16* dst = g_abT + (size_t)(g1_m * BM + wg * 64) * 2048 + g1_n * BN;
            store_tile_bf16(pk, smem + STG1_OFF + wg * STG_WG_BYTES, dst, 2048, wtid, 3 + wg);
        }
        asm volatile("bar.arrive 6, 288;" ::: "memory");
        TSTAMP(2);
        named_bar_sync(1, 256);
        conv_phase(p, smem, bid * 8, ctid, hv, kvr);
        asm volatile("fence.proxy.async.shared::cta;" ::: "memory");
        __syncwarp();
        release_stage(empty0, emptyA, emptyB, 2);
        release_stage(empty0, emptyA, emptyB, 3);
        named_bar_sync(1, 256);
        if (ctid == 0) asm volatile("red.release.gpu.global.add.u32 [%0], 1;" ::"l"(&g_sync[2]) : "memory");
        TSTAMP(3);
#pragma unroll
        for (int i = 0; i < 128; ++i) acc[i] = 0.f;
        gemm_consume(ps, acc, sbase, full0, empty0, emptyA, emptyB, wg, S_LEN / BK, 0);
        named_bar_sync(1, 256);
        TSTAMP(4);
        asm volatile("barrier.cluster.arrive.release.aligned;\n barrier.cluster.wait.acquire.aligned;" ::: "memory");
        uint32_t pk[64];
#pragma unroll
        for (int i = 0; i < 64; ++i) pk[i] = pack_bf16(acc[2 * i], acc[2 * i + 1]);
        const uint32_t xbuf = sbase + 2 * STG_WG_BYTES + 1024;
        const bool sender = (wg != part);
        if (sender) {
            uint32_t remote;
            remote = mapa_u32(xbuf, rank ^ 1);
#pragma unroll
            for (int i = 0; i < 64; ++i) {
                asm volatile("st.shared::cluster.b32 [%0], %1;" ::"r"(remote + (uint32_t)(i * 512 + wtid * 4)), "r"(pk[i]) : "memory");
            }
        }
        asm volatile("barrier.cluster.arrive.release.aligned;\n barrier.cluster.wait.acquire.aligned;" ::: "memory");
        if (!sender) {
#pragma unroll
            for (int i = 0; i < 64; ++i) {
                uint32_t o = lds32(xbuf + (uint32_t)(i * 512 + wtid * 4));
                uint32_t re = part ? o : pk[i];
                uint32_t im = part ? pk[i] : o;
                pk[i] = pack_bf16(bf_lo(re) - bf_lo(im), bf_hi(re) - bf_hi(im));
            }
            __nv_bfloat16* dst = p.out + (size_t)(g2_m * BM + wg * 64) * 2048 + g2_n * BN;
            store_tile_bf16(pk, smem + wg * STG_WG_BYTES, dst, 2048, wtid, 3 + wg);
        }
        TSTAMP(5);
    }
}

typedef CUresult (*PFN_encodeTiled)(CUtensorMap*, CUtensorMapDataType, cuuint32_t, void*, const cuuint64_t*,
                                    const cuuint64_t*, const cuuint32_t*, const cuuint32_t*, CUtensorMapInterleave,
                                    CUtensorMapSwizzle, CUtensorMapL2promotion, CUtensorMapFloatOOBfill);

static void make_map(PFN_encodeTiled enc, CUtensorMap* m, const void* ptr, int rows, int cols, int box_rows) {
    cuuint64_t gdim[2] = {(cuuint64_t)cols, (cuuint64_t)rows};
    cuuint64_t gstr[1] = {(cuuint64_t)cols * 2};
    cuuint32_t box[2] = {64, (cuuint32_t)box_rows};
    cuuint32_t estr[2] = {1, 1};
    enc(m, CU_TENSOR_MAP_DATA_TYPE_BFLOAT16, 2, const_cast<void*>(ptr), gdim, gstr, box, estr,
        CU_TENSOR_MAP_INTERLEAVE_NONE, CU_TENSOR_MAP_SWIZZLE_128B, CU_TENSOR_MAP_L2_PROMOTION_L2_256B,
        CU_TENSOR_MAP_FLOAT_OOB_FILL_NONE);
}

extern "C" void kernel_launch(void* const* d_in, const int* in_sizes, int n_in, void* d_out, int out_size) {
    static PFN_encodeTiled enc = nullptr;
    static bool attr_set = false;
    if (!enc) {
        void* fn = nullptr;
        cudaDriverEntryPointQueryResult qres;
        cudaGetDriverEntryPoint("cuTensorMapEncodeTiled", &fn, cudaEnableDefault, &qres);
        enc = (PFN_encodeTiled)fn;
    }
    if (!attr_set) {
        cudaFuncSetAttribute(fused_kernel, cudaFuncAttributeMaxDynamicSharedMemorySize, SMEM_BYTES);
        attr_set = true;
    }
    void* abT = nullptr;
    cudaGetSymbolAddress(&abT, g_abT);

    CUtensorMap mWre, mWim, mX, mAB, mCr, mCi;
    make_map(enc, &mX, d_in[0], 2048, 1024, BN / 2);
    make_map(enc, &mCr, d_in[1], 2048, 2048, BM / 2);
    make_map(enc, &mCi, d_in[2], 2048, 2048, BM / 2);
    make_map(enc, &mWre, d_in[3], 1024, 1024, BM / 2);
    make_map(enc, &mWim, d_in[4], 1024, 1024, BM / 2);
    make_map(enc, &mAB, abT, 2048, 2048, BN / 2);

    Params p;
    p.q = (const __nv_bfloat16*)d_in[5];
    p.k = (const __nv_bfloat16*)d_in[6];
    p.v = (const __nv_bfloat16*)d_in[7];
    p.shift_k = (const __nv_bfloat16*)d_in[8];
    p.ssm_k = (const __nv_bfloat16*)d_in[9];
    p.ssm_D = (const __nv_bfloat16*)d_in[10];
    p.out = (__nv_bfloat16*)d_out;

    fused_kernel<<<128, NTHREADS, SMEM_BYTES>>>(mWre, mWim, mX, mAB, mCr, mCi, p);
}
```

```cpp
#include <cuda_runtime.h>
#include <cuda_bf16.h>
#include <cuda.h>
#include <stdint.h>

#define S_LEN 2048
#define D_DIM 1024

__device__ __nv_bfloat16 g_abT[2048 * 2048];
__device__ unsigned int g_ready[8];
__device__ unsigned int g_passed[8];
__device__ __nv_bfloat16 g_kvT[1024 * 2048];
__device__ __nv_bfloat16 g_yT[1024 * 2048];
__device__ unsigned int g_sync[4];
#define TSTAMP(i)
#define TSTAMP2(i)

__device__ __forceinline__ uint32_t smem_u32(const void* p) {
    return (uint32_t)__cvta_generic_to_shared(p);
}
__device__ __forceinline__ void mbar_init(uint32_t bar, uint32_t count) {
    asm volatile("mbarrier.init.shared::cta.b64 [%0], %1;" ::"r"(bar), "r"(count));
}
__device__ __forceinline__ void mbar_expect_tx(uint32_t bar, uint32_t bytes) {
    asm volatile("mbarrier.arrive.expect_tx.shared::cta.b64 _, [%0], %1;" ::"r"(bar), "r"(bytes) : "memory");
}
__device__ __forceinline__ void mbar_arrive(uint32_t bar) {
    asm volatile("mbarrier.arrive.shared::cta.b64 _, [%0];" ::"r"(bar) : "memory");
}
__device__ __forceinline__ void mbar_wait(uint32_t bar, uint32_t parity) {
    asm volatile(
        "{\n"
        ".reg .pred p;\n"
        "LAB_WAIT:\n"
        "mbarrier.try_wait.parity.shared::cta.b64 p, [%0], %1;\n"
        "@p bra DONE;\n"
        "bra LAB_WAIT;\n"
        "DONE:\n"
        "}\n" ::"r"(bar), "r"(parity) : "memory");
}
__device__ __forceinline__ void tma_load_2d(uint32_t dst, const CUtensorMap* map, uint32_t bar, int c0, int c1) {
    asm volatile(
        "cp.async.bulk.tensor.2d.shared::cluster.global.mbarrier::complete_tx::bytes [%0], [%1, {%3, %4}], [%2];"
        ::"r"(dst), "l"((uint64_t)map), "r"(bar), "r"(c0), "r"(c1) : "memory");
}
__device__ __forceinline__ void tma_load_2d_mc(uint32_t dst, const CUtensorMap* map, uint32_t bar, int c0, int c1,
                                               uint16_t mask) {
    asm volatile(
        "cp.async.bulk.tensor.2d.shared::cluster.global.mbarrier::complete_tx::bytes.multicast::cluster "
        "[%0], [%1, {%3, %4}], [%2], %5;"
        ::"r"(dst), "l"((uint64_t)map), "r"(bar), "r"(c0), "r"(c1), "h"(mask) : "memory");
}
__device__ __forceinline__ uint32_t mapa_u32(uint32_t addr, uint32_t rank) {
    uint32_t r;
    asm volatile("mapa.shared::cluster.u32 %0, %1, %2;" : "=r"(r) : "r"(addr), "r"(rank));
    return r;
}
__device__ __forceinline__ void mbar_arrive_cluster(uint32_t remote_bar) {
    asm volatile("mbarrier.arrive.shared::cluster.b64 _, [%0];" ::"r"(remote_bar) : "memory");
}
__device__ __forceinline__ void cluster_sync_all() {
    asm volatile("barrier.cluster.arrive.release.aligned;\n barrier.cluster.wait.acquire.aligned;" ::: "memory");
}
__device__ __forceinline__ void wgmma_fence() { asm volatile("wgmma.fence.sync.aligned;" ::: "memory"); }
__device__ __forceinline__ void wgmma_commit() { asm volatile("wgmma.commit_group.sync.aligned;" ::: "memory"); }
template <int N>
__device__ __forceinline__ void wgmma_wait() { asm volatile("wgmma.wait_group.sync.aligned %0;" ::"n"(N) : "memory"); }

__device__ __forceinline__ uint64_t make_desc_sw128(uint32_t saddr) {
    uint64_t d = 0;
    d |= (uint64_t)((saddr & 0x3FFFF) >> 4);
    d |= (uint64_t)1 << 16;
    d |= (uint64_t)64 << 32;
    d |= (uint64_t)1 << 62;
    return d;
}

#define ACC8(a, i) "+f"(a[i]), "+f"(a[i + 1]), "+f"(a[i + 2]), "+f"(a[i + 3]), "+f"(a[i + 4]), "+f"(a[i + 5]), "+f"(a[i + 6]), "+f"(a[i + 7])

__device__ __forceinline__ void wgmma_m64n256k16(float (&d)[128], uint64_t da, uint64_t db, int scale_d) {
    asm volatile(
        "{\n"
        ".reg .pred p;\n"
        "setp.ne.b32 p, %130, 0;\n"
        "wgmma.mma_async.sync.aligned.m64n256k16.f32.bf16.bf16 "
        "{%0, %1, %2, %3, %4, %5, %6, %7, %8, %9, %10, %11, %12, %13, %14, %15, "
        "%16, %17, %18, %19, %20, %21, %22, %23, %24, %25, %26, %27, %28, %29, %30, %31, "
        "%32, %33, %34, %35, %36, %37, %38, %39, %40, %41, %42, %43, %44, %45, %46, %47, "
        "%48, %49, %50, %51, %52, %53, %54, %55, %56, %57, %58, %59, %60, %61, %62, %63, "
        "%64, %65, %66, %67, %68, %69, %70, %71, %72, %73, %74, %75, %76, %77, %78, %79, "
        "%80, %81, %82, %83, %84, %85, %86, %87, %88, %89, %90, %91, %92, %93, %94, %95, "
        "%96, %97, %98, %99, %100, %101, %102, %103, %104, %105, %106, %107, %108, %109, %110, %111, "
        "%112, %113, %114, %115, %116, %117, %118, %119, %120, %121, %122, %123, %124, %125, %126, %127}, "
        "%128, %129, p, 1, 1, 0, 0;\n"
        "}\n"
        : ACC8(d, 0), ACC8(d, 8), ACC8(d, 16), ACC8(d, 24), ACC8(d, 32), ACC8(d, 40), ACC8(d, 48), ACC8(d, 56),
          ACC8(d, 64), ACC8(d, 72), ACC8(d, 80), ACC8(d, 88), ACC8(d, 96), ACC8(d, 104), ACC8(d, 112), ACC8(d, 120)
        : "l"(da), "l"(db), "r"(scale_d));
}

__device__ __forceinline__ void wgmma_rs_n128(float (&d)[64], uint32_t a0, uint32_t a1, uint32_t a2, uint32_t a3,
                                              uint64_t db) {
    asm volatile(
        "wgmma.mma_async.sync.aligned.m64n128k16.f32.bf16.bf16 {%0, %1, %2, %3, %4, %5, %6, %7, %8, %9, %10, %11, %12, %13, %14, %15, %16, %17, %18, %19, %20, %21, %22, %23, %24, %25, %26, %27, %28, %29, %30, %31, %32, %33, %34, %35, %36, %37, %38, %39, %40, %41, %42, %43, %44, %45, %46, %47, %48, %49, %50, %51, %52, %53, %54, %55, %56, %57, %58, %59, %60, %61, %62, %63}, {%64, %65, %66, %67}, %68, 1, 1, 1, 0;\n"
        : "+f"(d[0]), "+f"(d[1]), "+f"(d[2]), "+f"(d[3]), "+f"(d[4]), "+f"(d[5]), "+f"(d[6]), "+f"(d[7]), "+f"(d[8]), "+f"(d[9]), "+f"(d[10]), "+f"(d[11]), "+f"(d[12]), "+f"(d[13]), "+f"(d[14]), "+f"(d[15]), "+f"(d[16]), "+f"(d[17]), "+f"(d[18]), "+f"(d[19]), "+f"(d[20]), "+f"(d[21]), "+f"(d[22]), "+f"(d[23]), "+f"(d[24]), "+f"(d[25]), "+f"(d[26]), "+f"(d[27]), "+f"(d[28]), "+f"(d[29]), "+f"(d[30]), "+f"(d[31]), "+f"(d[32]), "+f"(d[33]), "+f"(d[34]), "+f"(d[35]), "+f"(d[36]), "+f"(d[37]), "+f"(d[38]), "+f"(d[39]), "+f"(d[40]), "+f"(d[41]), "+f"(d[42]), "+f"(d[43]), "+f"(d[44]), "+f"(d[45]), "+f"(d[46]), "+f"(d[47]), "+f"(d[48]), "+f"(d[49]), "+f"(d[50]), "+f"(d[51]), "+f"(d[52]), "+f"(d[53]), "+f"(d[54]), "+f"(d[55]), "+f"(d[56]), "+f"(d[57]), "+f"(d[58]), "+f"(d[59]), "+f"(d[60]), "+f"(d[61]), "+f"(d[62]), "+f"(d[63])
        : "r"(a0), "r"(a1), "r"(a2), "r"(a3), "l"(db));
}
__device__ __forceinline__ void wgmma_rs_n96(float (&d)[64], uint32_t a0, uint32_t a1, uint32_t a2, uint32_t a3,
                                              uint64_t db) {
    asm volatile(
        "wgmma.mma_async.sync.aligned.m64n96k16.f32.bf16.bf16 {%0, %1, %2, %3, %4, %5, %6, %7, %8, %9, %10, %11, %12, %13, %14, %15, %16, %17, %18, %19, %20, %21, %22, %23, %24, %25, %26, %27, %28, %29, %30, %31, %32, %33, %34, %35, %36, %37, %38, %39, %40, %41, %42, %43, %44, %45, %46, %47}, {%48, %49, %50, %51}, %52, 1, 1, 1, 0;\n"
        : "+f"(d[16]), "+f"(d[17]), "+f"(d[18]), "+f"(d[19]), "+f"(d[20]), "+f"(d[21]), "+f"(d[22]), "+f"(d[23]), "+f"(d[24]), "+f"(d[25]), "+f"(d[26]), "+f"(d[27]), "+f"(d[28]), "+f"(d[29]), "+f"(d[30]), "+f"(d[31]), "+f"(d[32]), "+f"(d[33]), "+f"(d[34]), "+f"(d[35]), "+f"(d[36]), "+f"(d[37]), "+f"(d[38]), "+f"(d[39]), "+f"(d[40]), "+f"(d[41]), "+f"(d[42]), "+f"(d[43]), "+f"(d[44]), "+f"(d[45]), "+f"(d[46]), "+f"(d[47]), "+f"(d[48]), "+f"(d[49]), "+f"(d[50]), "+f"(d[51]), "+f"(d[52]), "+f"(d[53]), "+f"(d[54]), "+f"(d[55]), "+f"(d[56]), "+f"(d[57]), "+f"(d[58]), "+f"(d[59]), "+f"(d[60]), "+f"(d[61]), "+f"(d[62]), "+f"(d[63])
        : "r"(a0), "r"(a1), "r"(a2), "r"(a3), "l"(db));
}
__device__ __forceinline__ void wgmma_rs_n64(float (&d)[64], uint32_t a0, uint32_t a1, uint32_t a2, uint32_t a3,
                                              uint64_t db) {
    asm volatile(
        "wgmma.mma_async.sync.aligned.m64n64k16.f32.bf16.bf16 {%0, %1, %2, %3, %4, %5, %6, %7, %8, %9, %10, %11, %12, %13, %14, %15, %16, %17, %18, %19, %20, %21, %22, %23, %24, %25, %26, %27, %28, %29, %30, %31}, {%32, %33, %34, %35}, %36, 1, 1, 1, 0;\n"
        : "+f"(d[32]), "+f"(d[33]), "+f"(d[34]), "+f"(d[35]), "+f"(d[36]), "+f"(d[37]), "+f"(d[38]), "+f"(d[39]), "+f"(d[40]), "+f"(d[41]), "+f"(d[42]), "+f"(d[43]), "+f"(d[44]), "+f"(d[45]), "+f"(d[46]), "+f"(d[47]), "+f"(d[48]), "+f"(d[49]), "+f"(d[50]), "+f"(d[51]), "+f"(d[52]), "+f"(d[53]), "+f"(d[54]), "+f"(d[55]), "+f"(d[56]), "+f"(d[57]), "+f"(d[58]), "+f"(d[59]), "+f"(d[60]), "+f"(d[61]), "+f"(d[62]), "+f"(d[63])
        : "r"(a0), "r"(a1), "r"(a2), "r"(a3), "l"(db));
}
__device__ __forceinline__ void wgmma_rs_n32(float (&d)[64], uint32_t a0, uint32_t a1, uint32_t a2, uint32_t a3,
                                              uint64_t db) {
    asm volatile(
        "wgmma.mma_async.sync.aligned.m64n32k16.f32.bf16.bf16 {%0, %1, %2, %3, %4, %5, %6, %7, %8, %9, %10, %11, %12, %13, %14, %15}, {%16, %17, %18, %19}, %20, 1, 1, 1, 0;\n"
        : "+f"(d[48]), "+f"(d[49]), "+f"(d[50]), "+f"(d[51]), "+f"(d[52]), "+f"(d[53]), "+f"(d[54]), "+f"(d[55]), "+f"(d[56]), "+f"(d[57]), "+f"(d[58]), "+f"(d[59]), "+f"(d[60]), "+f"(d[61]), "+f"(d[62]), "+f"(d[63])
        : "r"(a0), "r"(a1), "r"(a2), "r"(a3), "l"(db));
}

__device__ __forceinline__ void mma_bf16_16816(float (&c)[4], uint32_t a0, uint32_t a1, uint32_t a2, uint32_t a3,
                                               uint32_t b0, uint32_t b1) {
    asm volatile(
        "mma.sync.aligned.m16n8k16.row.col.f32.bf16.bf16.f32 {%0,%1,%2,%3}, {%4,%5,%6,%7}, {%8,%9}, {%0,%1,%2,%3};"
        : "+f"(c[0]), "+f"(c[1]), "+f"(c[2]), "+f"(c[3])
        : "r"(a0), "r"(a1), "r"(a2), "r"(a3), "r"(b0), "r"(b1));
}

__device__ __forceinline__ uint32_t lds32(uint32_t addr) {
    uint32_t v;
    asm volatile("ld.shared.b32 %0, [%1];" : "=r"(v) : "r"(addr));
    return v;
}
__device__ __forceinline__ uint32_t pack_bf16(float lo, float hi) {
    __nv_bfloat162 t = __floats2bfloat162_rn(lo, hi);
    return *reinterpret_cast<uint32_t*>(&t);
}
__device__ __forceinline__ float bf_lo(uint32_t v) { return __uint_as_float(v << 16); }
__device__ __forceinline__ float bf_hi(uint32_t v) { return __uint_as_float(v & 0xffff0000u); }
__device__ __forceinline__ __nv_bfloat162 u2b(uint32_t v) { return *reinterpret_cast<__nv_bfloat162*>(&v); }
__device__ __forceinline__ uint32_t b2u(__nv_bfloat162 v) { return *reinterpret_cast<uint32_t*>(&v); }
__device__ __forceinline__ float rbf(float x) { return __bfloat162float(__float2bfloat16_rn(x)); }

__device__ __forceinline__ void named_bar_sync(int id, int n) {
    asm volatile("bar.sync %0, %1;" ::"r"(id), "r"(n) : "memory");
}

constexpr int BM = 128, BN = 256, BK = 64, STAGES = 4;
constexpr int A_BYTES = BM * BK * 2;
constexpr int B_BYTES = BN * BK * 2;
constexpr int STAGE_BYTES = A_BYTES + B_BYTES;
constexpr int SMEM_BYTES = STAGES * STAGE_BYTES + 34688 + 1024;
constexpr int NTHREADS = 384;

constexpr int STG_PITCH = 528;
constexpr int STG_WG_BYTES = 64 * STG_PITCH;

constexpr int KV_PITCH = 112 + 2048 + 8;
constexpr int KV_BYTES = 8 * KV_PITCH * 2;
constexpr int REV_PITCH = 2096;
constexpr int REV_BYTES = 8 * 2 * REV_PITCH * 2;
constexpr int YS_BYTES = 2048 * 8 * 2;
constexpr int CONV_KV_OFF = STAGES * STAGE_BYTES;
constexpr int CONV_REV_OFF = 2 * STAGE_BYTES;
constexpr int STG1_OFF = 2 * STAGE_BYTES;
constexpr int CONV_YS_OFF = CONV_REV_OFF + REV_BYTES;
static_assert(CONV_REV_OFF + REV_BYTES <= STAGES * STAGE_BYTES && STG1_OFF + 2 * STG_WG_BYTES <= STAGES * STAGE_BYTES && KV_BYTES <= 34688, "conv smem");
constexpr int PL_PAD = 32;
constexpr int PLANE_BYTES = (PL_PAD + 128) * 16;
constexpr int KVP_BYTES = 2 * PLANE_BYTES;
constexpr int KVP_OFF_HI = CONV_REV_OFF + REV_BYTES;
static_assert(6 * KVP_BYTES <= 34688 && KVP_OFF_HI + 2 * KVP_BYTES <= STAGES * STAGE_BYTES, "kv planes");
constexpr int YP = 131;
static_assert(16 * YP * 4 <= 2 * REV_PITCH * 2, "Y buffer");
constexpr int REV_Y0 = 2054;

struct Params {
    const __nv_bfloat16 *q, *k, *v, *shift_k, *ssm_k, *ssm_D;
    __nv_bfloat16* out;
};

struct PipeState {
    int stage;
    uint32_t phase;
    __device__ __forceinline__ void advance() {
        if (++stage == STAGES) { stage = 0; phase ^= 1; }
    }
};

template <bool B_MC>
__device__ __forceinline__ void gemm_produce(PipeState& ps, uint32_t sbase, uint32_t full0, uint32_t empty0,
                                             const CUtensorMap* mA, const CUtensorMap* mB, int arow, int brow,
                                             int ahalf, int bhalf, uint16_t maskA, uint16_t maskB, int k0, int nk) {
#pragma unroll 1
    for (int it = k0; it < nk; ++it) {
        mbar_wait(empty0 + 8 * ps.stage, ps.phase ^ 1);
        uint32_t fb = full0 + 8 * ps.stage;
        mbar_expect_tx(fb, STAGE_BYTES);
        uint32_t sa = sbase + ps.stage * STAGE_BYTES;
        tma_load_2d(sa, mA, fb, it * BK, arow);
        tma_load_2d(sa + A_BYTES / 2, mA, fb, it * BK, arow + BM / 2);
        if (B_MC) {
            tma_load_2d_mc(sa + A_BYTES + bhalf * (B_BYTES / 2), mB, fb, it * BK, brow + bhalf * (BN / 2), maskB);
        } else {
            tma_load_2d(sa + A_BYTES, mB, fb, it * BK, brow);
            tma_load_2d(sa + A_BYTES + B_BYTES / 2, mB, fb, it * BK, brow + BN / 2);
        }
        ps.advance();
    }
}

__device__ __forceinline__ void release_stage(uint32_t empty0, uint32_t emptyA, uint32_t emptyB, int stage) {
    if ((threadIdx.x & 31) == 0) {
        mbar_arrive(empty0 + 8 * stage);
        mbar_arrive_cluster(emptyB + 8 * stage);
    }
}

__device__ __forceinline__ void gemm_consume(PipeState& ps, float (&acc)[128], uint32_t sbase, uint32_t full0,
                                             uint32_t empty0, uint32_t emptyA, uint32_t emptyB, int wg, int nk,
                                             int n_hold) {
    int prev_stage = -1;
#pragma unroll 1
    for (int it = 0; it < nk; ++it) {
        mbar_wait(full0 + 8 * ps.stage, ps.phase);
        uint32_t sa = sbase + ps.stage * STAGE_BYTES + wg * (64 * 128);
        uint32_t sb = sbase + ps.stage * STAGE_BYTES + A_BYTES;
        uint64_t da = make_desc_sw128(sa);
        uint64_t db = make_desc_sw128(sb);
        wgmma_fence();
#pragma unroll
        for (int kk = 0; kk < 4; ++kk) {
            wgmma_m64n256k16(acc, da + (uint64_t)(kk * 2), db + (uint64_t)(kk * 2), (it > 0 || kk > 0) ? 1 : 0);
        }
        wgmma_commit();
        if (prev_stage >= 0) {
            wgmma_wait<1>();
            if (it - 1 < nk - n_hold) release_stage(empty0, emptyA, emptyB, prev_stage);
        }
        prev_stage = ps.stage;
        ps.advance();
    }
    wgmma_wait<0>();
    if (n_hold == 0) release_stage(empty0, emptyA, emptyB, prev_stage);
}

__device__ __forceinline__ void store_tile_bf16(const uint32_t (&pk)[64], uint8_t* stg, __nv_bfloat16* gdst, int ld,
                                                int wg_tid, int bar_id) {
    const int warp = wg_tid >> 5, lane = wg_tid & 31;
    const int r0 = warp * 16 + (lane >> 2);
    const int c0 = (lane & 3) * 2;
#pragma unroll
    for (int j = 0; j < 32; ++j) {
        *reinterpret_cast<uint32_t*>(stg + r0 * STG_PITCH + (j * 8 + c0) * 2) = pk[2 * j];
        *reinterpret_cast<uint32_t*>(stg + (r0 + 8) * STG_PITCH + (j * 8 + c0) * 2) = pk[2 * j + 1];
    }
    named_bar_sync(bar_id, 128);
#pragma unroll
    for (int p = 0; p < 16; ++p) {
        int r = p * 4 + (wg_tid >> 5);
        int cb = (wg_tid & 31) * 16;
        uint4 val = *reinterpret_cast<const uint4*>(stg + r * STG_PITCH + cb);
        *reinterpret_cast<uint4*>(reinterpret_cast<uint8_t*>(gdst + (size_t)r * ld) + cb) = val;
    }
}

__device__ __forceinline__ void counter_wait(unsigned int* ready, unsigned int* passed, unsigned int n_ready,
                                             unsigned int n_wait) {
    unsigned int v;
    long long spins = 0;
    do {
        asm volatile("ld.acquire.gpu.global.u32 %0, [%1];" : "=r"(v) : "l"(ready) : "memory");
    } while (v < n_ready && ++spins < (1ll << 26));
    unsigned int old = atomicAdd(passed, 1u);
    if (old == n_wait - 1) {
        *passed = 0;
        *ready = 0;
        __threadfence();
    }
}

__device__ __forceinline__ void kv_prepass(const Params& p, int s0, int ctid) {
    const int c0 = ctid * 4;
    uint2 kr[19], vr[16];
#pragma unroll
    for (int j = 0; j < 19; ++j) {
        int s = s0 - 3 + j;
        if (s >= 0) kr[j] = __ldg(reinterpret_cast<const uint2*>(p.k + (size_t)s * D_DIM + c0));
        else kr[j] = make_uint2(0, 0);
    }
#pragma unroll
    for (int j = 0; j < 16; ++j) vr[j] = __ldg(reinterpret_cast<const uint2*>(p.v + (size_t)(s0 + j) * D_DIM + c0));
    uint4 w0 = __ldg(reinterpret_cast<const uint4*>(p.shift_k + (size_t)c0 * 4));
    uint4 w1 = __ldg(reinterpret_cast<const uint4*>(p.shift_k + (size_t)c0 * 4 + 8));
    uint32_t wt[2][4];
    wt[0][0] = __byte_perm(w0.x, w0.z, 0x5410); wt[0][1] = __byte_perm(w0.x, w0.z, 0x7632);
    wt[0][2] = __byte_perm(w0.y, w0.w, 0x5410); wt[0][3] = __byte_perm(w0.y, w0.w, 0x7632);
    wt[1][0] = __byte_perm(w1.x, w1.z, 0x5410); wt[1][1] = __byte_perm(w1.x, w1.z, 0x7632);
    wt[1][2] = __byte_perm(w1.y, w1.w, 0x5410); wt[1][3] = __byte_perm(w1.y, w1.w, 0x7632);
#pragma unroll
    for (int pr = 0; pr < 2; ++pr) {
        uint32_t r[16];
#pragma unroll
        for (int j = 0; j < 16; ++j) {
            __nv_bfloat162 k0 = u2b(pr ? kr[j].y : kr[j].x), k1 = u2b(pr ? kr[j + 1].y : kr[j + 1].x);
            __nv_bfloat162 k2 = u2b(pr ? kr[j + 2].y : kr[j + 2].x), k3 = u2b(pr ? kr[j + 3].y : kr[j + 3].x);
            __nv_bfloat162 acc = __hmul2(k0, u2b(wt[pr][3]));
            acc = __hadd2(acc, __hmul2(k1, u2b(wt[pr][2])));
            acc = __hadd2(acc, __hmul2(k2, u2b(wt[pr][1])));
            acc = __hadd2(acc, __hmul2(k3, u2b(wt[pr][0])));
            acc = __hmul2(acc, u2b(pr ? vr[j].y : vr[j].x));
            r[j] = b2u(acc);
        }
        uint32_t lo[8], hi[8];
#pragma unroll
        for (int j = 0; j < 8; ++j) {
            lo[j] = __byte_perm(r[2 * j], r[2 * j + 1], 0x5410);
            hi[j] = __byte_perm(r[2 * j], r[2 * j + 1], 0x7632);
        }
        uint4* d0 = reinterpret_cast<uint4*>(g_kvT + (size_t)(c0 + 2 * pr) * S_LEN + s0);
        uint4* d1 = reinterpret_cast<uint4*>(g_kvT + (size_t)(c0 + 2 * pr + 1) * S_LEN + s0);
        d0[0] = make_uint4(lo[0], lo[1], lo[2], lo[3]);
        d0[1] = make_uint4(lo[4], lo[5], lo[6], lo[7]);
        d1[0] = make_uint4(hi[0], hi[1], hi[2], hi[3]);
        d1[1] = make_uint4(hi[4], hi[5], hi[6], hi[7]);
    }
}

__device__ __forceinline__ void out_postpass(const Params& p, int s0, int ctid) {
    const int c0 = ctid * 4;
    uint2 qr[16];
#pragma unroll
    for (int j = 0; j < 16; ++j) qr[j] = __ldg(reinterpret_cast<const uint2*>(p.q + (size_t)(s0 + j) * D_DIM + c0));
    uint4 yy[4][2];
#pragma unroll
    for (int c = 0; c < 4; ++c) {
        const uint4* src = reinterpret_cast<const uint4*>(g_yT + (size_t)(c0 + c) * S_LEN + s0);
        yy[c][0] = __ldcg(src);
        yy[c][1] = __ldcg(src + 1);
    }
#pragma unroll
    for (int j = 0; j < 16; j += 2) {
        uint32_t y0 = reinterpret_cast<const uint32_t*>(&yy[0][0])[j >> 1], y1 = reinterpret_cast<const uint32_t*>(&yy[1][0])[j >> 1];
        uint32_t y2 = reinterpret_cast<const uint32_t*>(&yy[2][0])[j >> 1], y3 = reinterpret_cast<const uint32_t*>(&yy[3][0])[j >> 1];
        uint2 o;
        o.x = b2u(__hmul2(u2b(qr[j].x), u2b(__byte_perm(y0, y1, 0x5410))));
        o.y = b2u(__hmul2(u2b(qr[j].y), u2b(__byte_perm(y2, y3, 0x5410))));
        *reinterpret_cast<uint2*>(p.out + (size_t)(s0 + j) * 2048 + 1024 + c0) = o;
        o.x = b2u(__hmul2(u2b(qr[j + 1].x), u2b(__byte_perm(y0, y1, 0x7632))));
        o.y = b2u(__hmul2(u2b(qr[j + 1].y), u2b(__byte_perm(y2, y3, 0x7632))));
        *reinterpret_cast<uint2*>(p.out + (size_t)(s0 + j + 1) * 2048 + 1024 + c0) = o;
    }
}

__device__ __forceinline__ void conv_phase(const Params& p, uint8_t* smem, int ch0, int ctid, const uint4 (&hv)[8], const uint4 (&t)[8]) {
    const int warp = ctid >> 5, lane = ctid & 31;
    __nv_bfloat16* kvs = reinterpret_cast<__nv_bfloat16*>(smem + CONV_KV_OFF) + (size_t)warp * KV_PITCH;
    __nv_bfloat16* rev = reinterpret_cast<__nv_bfloat16*>(smem + CONV_REV_OFF);

    {
        __nv_bfloat16* r0 = rev + (size_t)(warp * 2) * REV_PITCH;
        __nv_bfloat16* r1 = r0 + REV_PITCH;
        const unsigned short* hraw = reinterpret_cast<const unsigned short*>(p.ssm_k + (size_t)(ch0 + warp) * S_LEN);
#pragma unroll
        for (int it = 0; it < 8; ++it) {
            int idx = 8 * (lane + 32 * it);
            uint32_t prev = (idx > 0) ? (uint32_t)__ldg(hraw + idx - 1) : 0u;
            uint4 h4 = hv[it];
            uint4 o1, o0;
            o1.x = __byte_perm(h4.w, 0, 0x1032); o1.y = __byte_perm(h4.z, 0, 0x1032);
            o1.z = __byte_perm(h4.y, 0, 0x1032); o1.w = __byte_perm(h4.x, 0, 0x1032);
            *reinterpret_cast<uint4*>(r1 + (REV_Y0 - 6 - idx)) = o1;
            o0.x = __byte_perm(h4.w, h4.z, 0x7610);
            o0.y = __byte_perm(h4.z, h4.y, 0x7610);
            o0.z = __byte_perm(h4.y, h4.x, 0x7610);
            o0.w = __byte_perm(h4.x, prev, 0x5410);
            *reinterpret_cast<uint4*>(r0 + (REV_Y0 - 6 - idx)) = o0;
        }
        if (lane == 31) r0[REV_Y0 - 2047] = reinterpret_cast<const __nv_bfloat16*>(&hv[7])[7];
        if (lane < 24) {
            int idx = -1 - lane;
            r0[REV_Y0 - idx] = __float2bfloat16_rn(0.f);
            r1[REV_Y0 + 1 - idx] = __float2bfloat16_rn(0.f);
        }
    }
    {
        uint8_t* kp = smem + ((warp < 6) ? (CONV_KV_OFF + warp * KVP_BYTES) : (KVP_OFF_HI + (warp - 6) * KVP_BYTES));
#pragma unroll
        for (int it = 0; it < 8; ++it) {
            int c = lane + 32 * it;
            *reinterpret_cast<uint4*>(kp + (c & 1) * PLANE_BYTES + (PL_PAD + (c >> 1)) * 16) = t[it];
        }
        *reinterpret_cast<uint4*>(kp + lane * 16) = make_uint4(0, 0, 0, 0);
        *reinterpret_cast<uint4*>(kp + PLANE_BYTES + lane * 16) = make_uint4(0, 0, 0, 0);
    }
    asm volatile("fence.proxy.async.shared::cta;" ::: "memory");
    const int wg = ctid >> 7, w4 = warp & 3, wtid = ctid & 127;
    named_bar_sync(3 + wg, 128);
    TSTAMP(6);
    const int g = lane >> 2, c2 = (lane & 3) * 2;
#pragma unroll 1
    for (int cc = 0; cc < 4; ++cc) {
        const int ch = wg * 4 + cc;
        const uint32_t kp = smem_u32(smem) + (uint32_t)((ch < 6) ? (CONV_KV_OFF + ch * KVP_BYTES) : (KVP_OFF_HI + (ch - 6) * KVP_BYTES));
        const uint32_t rev_base = smem_u32(rev + (size_t)(ch * 2 + (g & 1)) * REV_PITCH) +
                                  2u * (uint32_t)(REV_Y0 + (g & 1) - g + c2 - 16 * w4);
        float acc[64];
#pragma unroll
        for (int i = 0; i < 64; ++i) acc[i] = 0.f;
        const uint64_t dbase = ((uint64_t)(PLANE_BYTES >> 4) << 16) | ((uint64_t)(128 >> 4) << 32);
#pragma unroll
        for (int qd = 0; qd < 4; ++qd) {
            uint32_t f[8][3];
#pragma unroll
            for (int st = 0; st < 8; ++st) {
                int delta = 16 * (32 * qd + 4 * st);
                f[st][0] = lds32(rev_base - 2u * (uint32_t)(delta - 8));
                f[st][1] = lds32(rev_base - 2u * (uint32_t)(delta));
                f[st][2] = lds32(rev_base - 2u * (uint32_t)(delta + 8));
            }
            wgmma_fence();
#pragma unroll
            for (int st = 0; st < 8; ++st) {
                uint32_t baddr = kp + (uint32_t)((PL_PAD - 4 * st) * 16);
                uint64_t db = dbase | (uint64_t)((baddr & 0x3FFFF) >> 4);
                if (qd == 0) wgmma_rs_n128(acc, f[st][1], f[st][2], f[st][0], f[st][1], db);
                else if (qd == 1) wgmma_rs_n96(acc, f[st][1], f[st][2], f[st][0], f[st][1], db);
                else if (qd == 2) wgmma_rs_n64(acc, f[st][1], f[st][2], f[st][0], f[st][1], db);
                else wgmma_rs_n32(acc, f[st][1], f[st][2], f[st][0], f[st][1], db);
            }
            wgmma_commit();
            if (qd & 1) wgmma_wait<0>();
        }
        named_bar_sync(3 + wg, 128);
        float* Y = reinterpret_cast<float*>(rev + (size_t)(ch * 2) * REV_PITCH);
        for (int i = wtid; i < 16 * YP; i += 128) Y[i] = 0.f;
        named_bar_sync(3 + wg, 128);
#pragma unroll
        for (int j = 0; j < 16; ++j) {
#pragma unroll
            for (int e = 0; e < 4; ++e) {
                int col = 8 * j + c2 + (e & 1) + w4;
                int row = g + 8 * (e >> 1);
                atomicAdd(&Y[row * YP + col], acc[4 * j + e]);
            }
        }
        named_bar_sync(3 + wg, 128);
        {
            const __nv_bfloat162 D2 = __bfloat162bfloat162(p.ssm_D[ch0 + ch]);
#pragma unroll
            for (int it = 0; it < 2; ++it) {
                int c = wtid + 128 * it;
                int n = c >> 1, hh = c & 1;
                uint4 kv4;
                asm volatile("ld.shared.v4.b32 {%0,%1,%2,%3}, [%4];" : "=r"(kv4.x), "=r"(kv4.y), "=r"(kv4.z), "=r"(kv4.w)
                             : "r"(kp + (uint32_t)(hh * PLANE_BYTES + (PL_PAD + n) * 16)));
                const uint32_t* kvw = reinterpret_cast<const uint32_t*>(&kv4);
                uint32_t o[4];
#pragma unroll
                for (int e = 0; e < 4; ++e) {
                    float y0 = Y[(8 * hh + 2 * e) * YP + n], y1 = Y[(8 * hh + 2 * e + 1) * YP + n];
                    __nv_bfloat162 yb = __floats2bfloat162_rn(y0, y1);
                    o[e] = b2u(__hadd2(yb, __hmul2(u2b(kvw[e]), D2)));
                }
                *reinterpret_cast<uint4*>(g_yT + (size_t)(ch0 + ch) * S_LEN + 8 * c) = make_uint4(o[0], o[1], o[2], o[3]);
            }
        }
    }
    TSTAMP(7);
}

__global__ void __cluster_dims__(2, 1, 1) __launch_bounds__(NTHREADS, 1)
fused_kernel(const __grid_constant__ CUtensorMap mWre, const __grid_constant__ CUtensorMap mWim,
             const __grid_constant__ CUtensorMap mX, const __grid_constant__ CUtensorMap mAB,
             const __grid_constant__ CUtensorMap mCr, const __grid_constant__ CUtensorMap mCi,
             const Params p) {
    extern __shared__ uint8_t smem_raw[];
    __shared__ __align__(8) uint64_t bars[2 * STAGES];
    uint8_t* smem = smem_raw + ((1024u - (smem_u32(smem_raw) & 1023u)) & 1023u);
    const uint32_t sbase = smem_u32(smem);
    const uint32_t full0 = smem_u32(&bars[0]);
    const uint32_t empty0 = smem_u32(&bars[STAGES]);
    const int tid = threadIdx.x;
    const int wgid = tid >> 7;
    const int bid = blockIdx.x;

    if (tid == 0) {
        for (int i = 0; i < STAGES; ++i) {
            mbar_init(full0 + 8 * i, 1);
            mbar_init(empty0 + 8 * i, 16);
        }
        asm volatile("fence.mbarrier_init.release.cluster;" ::: "memory");
    }
    __syncthreads();
    cluster_sync_all();

    const int rank = bid & 1, pair = bid >> 1;
    const int g1_m = 2 * (pair >> 3) + rank, g1_n = pair & 7;
    const int part = rank;
    const int g2_m = pair >> 2, g2_n = pair & 3;
    const int grp = part * 4 + g2_n;

    if (wgid == 0) {
        if (tid == 0) {
            PipeState ps{0, 0};
            const CUtensorMap* mW = (g1_m < 8) ? &mWre : &mWim;
            gemm_produce<true>(ps, sbase, full0, empty0, mW, &mX, (g1_m & 7) * BM, g1_n * BN, 0, rank, 0, 3, 0, D_DIM / BK);
        }
        if (tid >= 32) {
#pragma unroll 1
            for (int t = tid - 32; t < 256; t += 96) { kv_prepass(p, bid * 16, t); TSTAMP2(8 + t / 96); }
            named_bar_sync(5, 96);
            TSTAMP2(11);
            if (tid == 32) asm volatile("red.release.gpu.global.add.u32 [%0], 1;" ::"l"(&g_sync[0]) : "memory");
            if (tid < 64) {
                __syncwarp();
                named_bar_sync(6, 288);
                if (tid == 32) {
                    asm volatile("fence.proxy.async;" ::: "memory");
                    asm volatile("red.release.gpu.global.add.u32 [%0], 1;" ::"l"(&g_ready[g1_m >> 1]) : "memory");
                }
             }
        }
        const CUtensorMap* mC = part ? &mCi : &mCr;
        PipeState ps2{0, 0};
        if (tid == 0) {
            counter_wait(&g_ready[grp], &g_passed[grp], 16u, 16u);
            asm volatile("fence.proxy.async;" ::: "memory");
            gemm_produce<false>(ps2, sbase, full0, empty0, mC, &mAB, g2_m * BM, grp * BN, 0, 0, 0, 0, 0, 2);
#pragma unroll 1
            for (int it = g2_n * 8; it < g2_n * 8 + 8; ++it) {
                asm volatile("cp.async.bulk.prefetch.tensor.2d.L2.global [%0, {%1, %2}];" ::"l"((uint64_t)mC),
                             "r"(it * BK), "r"(g2_m * BM) : "memory");
                asm volatile("cp.async.bulk.prefetch.tensor.2d.L2.global [%0, {%1, %2}];" ::"l"((uint64_t)mC),
                             "r"(it * BK), "r"(g2_m * BM + 64) : "memory");
            }
        }
        if (tid == 0) {
            gemm_produce<false>(ps2, sbase, full0, empty0, mC, &mAB, g2_m * BM, grp * BN, 0, 0, 0, 0, 2, S_LEN / BK);
        }
        if (tid >= 32) {
            if (tid == 32) counter_wait(&g_sync[2], &g_sync[3], 128u, 128u);
            named_bar_sync(5, 96);
#pragma unroll 1
            for (int t = tid - 32; t < 256; t += 96) out_postpass(p, bid * 16, t);
        }
        __syncwarp();
        asm volatile("barrier.cluster.arrive.release.aligned;\n barrier.cluster.wait.acquire.aligned;" ::: "memory");
        asm volatile("barrier.cluster.arrive.release.aligned;\n barrier.cluster.wait.acquire.aligned;" ::: "memory");
    } else {
        const int wg = wgid - 1;
        const int ctid = tid - 128;
        const int wtid = tid & 127;
        PipeState ps{0, 0};
        float acc[128];
        const uint32_t emptyA = 0, emptyB = mapa_u32(empty0, rank ^ 1);
        TSTAMP(0);
        gemm_consume(ps, acc, sbase, full0, empty0, emptyA, emptyB, wg, D_DIM / BK, 2);
        named_bar_sync(1, 256);
        TSTAMP(1);
        uint4 hv[8], kvr[8];
        {
            uint32_t pk[64];
#pragma unroll
            for (int i = 0; i < 64; ++i) pk[i] = pack_bf16(acc[2 * i], acc[2 * i + 1]);
            if (ctid == 0) counter_wait(&g_sync[0], &g_sync[1], 128u, 128u);
            named_bar_sync(1, 256);
            {
                const int cw = ctid >> 5, cl = ctid & 31;
                const uint4* hs = reinterpret_cast<const uint4*>(p.ssm_k + (size_t)(bid * 8 + cw) * S_LEN);
                const uint4* ks = reinterpret_cast<const uint4*>(g_kvT + (size_t)(bid * 8 + cw) * S_LEN);
#pragma unroll
                for (int it = 0; it < 8; ++it) { hv[it] = __ldg(hs + cl + 32 * it); kvr[it] = __ldcg(ks + cl + 32 * it); }
            }
            __nv_bfloat16* dst = g_abT + (size_t)(g1_m * BM + wg * 64) * 2048 + g1_n * BN;
            store_tile_bf16(pk, smem + STG1_OFF + wg * STG_WG_BYTES, dst, 2048, wtid, 3 + wg);
        }
        asm volatile("bar.arrive 6, 288;" ::: "memory");
        TSTAMP(2);
        named_bar_sync(1, 256);
        conv_phase(p, smem, bid * 8, ctid, hv, kvr);
        asm volatile("fence.proxy.async.shared::cta;" ::: "memory");
        __syncwarp();
        release_stage(empty0, emptyA, emptyB, 2);
        release_stage(empty0, emptyA, emptyB, 3);
        named_bar_sync(1, 256);
        if (ctid == 0) asm volatile("red.release.gpu.global.add.u32 [%0], 1;" ::"l"(&g_sync[2]) : "memory");
        TSTAMP(3);
#pragma unroll
        for (int i = 0; i < 128; ++i) acc[i] = 0.f;
        gemm_consume(ps, acc, sbase, full0, empty0, emptyA, emptyB, wg, S_LEN / BK, 0);
        named_bar_sync(1, 256);
        TSTAMP(4);
        asm volatile("barrier.cluster.arrive.release.aligned;\n barrier.cluster.wait.acquire.aligned;" ::: "memory");
        uint32_t pk[64];
#pragma unroll
        for (int i = 0; i < 64; ++i) pk[i] = pack_bf16(acc[2 * i], acc[2 * i + 1]);
        const uint32_t xbuf = sbase + 2 * STG_WG_BYTES + 1024;
        const bool sender = (wg != part);
        if (sender) {
            uint32_t remote;
            remote = mapa_u32(xbuf, rank ^ 1);
#pragma unroll
            for (int i = 0; i < 64; ++i) {
                asm volatile("st.shared::cluster.b32 [%0], %1;" ::"r"(remote + (uint32_t)(i * 512 + wtid * 4)), "r"(pk[i]) : "memory");
            }
        }
        asm volatile("barrier.cluster.arrive.release.aligned;\n barrier.cluster.wait.acquire.aligned;" ::: "memory");
        if (!sender) {
#pragma unroll
            for (int i = 0; i < 64; ++i) {
                uint32_t o = lds32(xbuf + (uint32_t)(i * 512 + wtid * 4));
                uint32_t re = part ? o : pk[i];
                uint32_t im = part ? pk[i] : o;
                pk[i] = pack_bf16(bf_lo(re) - bf_lo(im), bf_hi(re) - bf_hi(im));
            }
            __nv_bfloat16* dst = p.out + (size_t)(g2_m * BM + wg * 64) * 2048 + g2_n * BN;
            store_tile_bf16(pk, smem + wg * STG_WG_BYTES, dst, 2048, wtid, 3 + wg);
        }
        TSTAMP(5);
    }
}

typedef CUresult (*PFN_encodeTiled)(CUtensorMap*, CUtensorMapDataType, cuuint32_t, void*, const cuuint64_t*,
                                    const cuuint64_t*, const cuuint32_t*, const cuuint32_t*, CUtensorMapInterleave,
                                    CUtensorMapSwizzle, CUtensorMapL2promotion, CUtensorMapFloatOOBfill);

static void make_map(PFN_encodeTiled enc, CUtensorMap* m, const void* ptr, int rows, int cols, int box_rows) {
    cuuint64_t gdim[2] = {(cuuint64_t)cols, (cuuint64_t)rows};
    cuuint64_t gstr[1] = {(cuuint64_t)cols * 2};
    cuuint32_t box[2] = {64, (cuuint32_t)box_rows};
    cuuint32_t estr[2] = {1, 1};
    enc(m, CU_TENSOR_MAP_DATA_TYPE_BFLOAT16, 2, const_cast<void*>(ptr), gdim, gstr, box, estr,
        CU_TENSOR_MAP_INTERLEAVE_NONE, CU_TENSOR_MAP_SWIZZLE_128B, CU_TENSOR_MAP_L2_PROMOTION_L2_256B,
        CU_TENSOR_MAP_FLOAT_OOB_FILL_NONE);
}

extern "C" void kernel_launch(void* const* d_in, const int* in_sizes, int n_in, void* d_out, int out_size) {
    static PFN_encodeTiled enc = nullptr;
    static bool attr_set = false;
    if (!enc) {
        void* fn = nullptr;
        cudaDriverEntryPointQueryResult qres;
        cudaGetDriverEntryPoint("cuTensorMapEncodeTiled", &fn, cudaEnableDefault, &qres);
        enc = (PFN_encodeTiled)fn;
    }
    if (!attr_set) {
        cudaFuncSetAttribute(fused_kernel, cudaFuncAttributeMaxDynamicSharedMemorySize, SMEM_BYTES);
        attr_set = true;
    }
    void* abT = nullptr;
    cudaGetSymbolAddress(&abT, g_abT);

    CUtensorMap mWre, mWim, mX, mAB, mCr, mCi;
    make_map(enc, &mX, d_in[0], 2048, 1024, BN / 2);
    make_map(enc, &mCr, d_in[1], 2048, 2048, BM / 2);
    make_map(enc, &mCi, d_in[2], 2048, 2048, BM / 2);
    make_map(enc, &mWre, d_in[3], 1024, 1024, BM / 2);
    make_map(enc, &mWim, d_in[4], 1024, 1024, BM / 2);
    make_map(enc, &mAB, abT, 2048, 2048, BN / 2);

    Params p;
    p.q = (const __nv_bfloat16*)d_in[5];
    p.k = (const __nv_bfloat16*)d_in[6];
    p.v = (const __nv_bfloat16*)d_in[7];
    p.shift_k = (const __nv_bfloat16*)d_in[8];
    p.ssm_k = (const __nv_bfloat16*)d_in[9];
    p.ssm_D = (const __nv_bfloat16*)d_in[10];
    p.out = (__nv_bfloat16*)d_out;

    fused_kernel<<<128, NTHREADS, SMEM_BYTES>>>(mWre, mWim, mX, mAB, mCr, mCi, p);
}
```

```cpp
#include <cuda_runtime.h>
#include <cuda_bf16.h>
#include <cuda.h>
#include <stdint.h>

#define S_LEN 2048
#define D_DIM 1024

__device__ __nv_bfloat16 g_abT[2048 * 2048];
__device__ unsigned int g_ready[8];
__device__ unsigned int g_passed[8];
__device__ __nv_bfloat16 g_kvT[1024 * 2048];
__device__ __nv_bfloat16 g_yT[1024 * 2048];
__device__ unsigned int g_sync[4];
#define TSTAMP(i)
#define TSTAMP2(i)

__device__ __forceinline__ uint32_t smem_u32(const void* p) {
    return (uint32_t)__cvta_generic_to_shared(p);
}
__device__ __forceinline__ void mbar_init(uint32_t bar, uint32_t count) {
    asm volatile("mbarrier.init.shared::cta.b64 [%0], %1;" ::"r"(bar), "r"(count));
}
__device__ __forceinline__ void mbar_expect_tx(uint32_t bar, uint32_t bytes) {
    asm volatile("mbarrier.arrive.expect_tx.shared::cta.b64 _, [%0], %1;" ::"r"(bar), "r"(bytes) : "memory");
}
__device__ __forceinline__ void mbar_arrive(uint32_t bar) {
    asm volatile("mbarrier.arrive.shared::cta.b64 _, [%0];" ::"r"(bar) : "memory");
}
__device__ __forceinline__ void mbar_wait(uint32_t bar, uint32_t parity) {
    asm volatile(
        "{\n"
        ".reg .pred p;\n"
        "LAB_WAIT:\n"
        "mbarrier.try_wait.parity.shared::cta.b64 p, [%0], %1;\n"
        "@p bra DONE;\n"
        "bra LAB_WAIT;\n"
        "DONE:\n"
        "}\n" ::"r"(bar), "r"(parity) : "memory");
}
__device__ __forceinline__ void tma_load_2d(uint32_t dst, const CUtensorMap* map, uint32_t bar, int c0, int c1) {
    asm volatile(
        "cp.async.bulk.tensor.2d.shared::cluster.global.mbarrier::complete_tx::bytes [%0], [%1, {%3, %4}], [%2];"
        ::"r"(dst), "l"((uint64_t)map), "r"(bar), "r"(c0), "r"(c1) : "memory");
}
__device__ __forceinline__ void tma_load_2d_mc(uint32_t dst, const CUtensorMap* map, uint32_t bar, int c0, int c1,
                                               uint16_t mask) {
    asm volatile(
        "cp.async.bulk.tensor.2d.shared::cluster.global.mbarrier::complete_tx::bytes.multicast::cluster "
        "[%0], [%1, {%3, %4}], [%2], %5;"
        ::"r"(dst), "l"((uint64_t)map), "r"(bar), "r"(c0), "r"(c1), "h"(mask) : "memory");
}
__device__ __forceinline__ uint32_t mapa_u32(uint32_t addr, uint32_t rank) {
    uint32_t r;
    asm volatile("mapa.shared::cluster.u32 %0, %1, %2;" : "=r"(r) : "r"(addr), "r"(rank));
    return r;
}
__device__ __forceinline__ void mbar_arrive_cluster(uint32_t remote_bar) {
    asm volatile("mbarrier.arrive.shared::cluster.b64 _, [%0];" ::"r"(remote_bar) : "memory");
}
__device__ __forceinline__ void cluster_sync_all() {
    asm volatile("barrier.cluster.arrive.release.aligned;\n barrier.cluster.wait.acquire.aligned;" ::: "memory");
}
__device__ __forceinline__ void wgmma_fence() { asm volatile("wgmma.fence.sync.aligned;" ::: "memory"); }
__device__ __forceinline__ void wgmma_commit() { asm volatile("wgmma.commit_group.sync.aligned;" ::: "memory"); }
template <int N>
__device__ __forceinline__ void wgmma_wait() { asm volatile("wgmma.wait_group.sync.aligned %0;" ::"n"(N) : "memory"); }

__device__ __forceinline__ uint64_t make_desc_sw128(uint32_t saddr) {
    uint64_t d = 0;
    d |= (uint64_t)((saddr & 0x3FFFF) >> 4);
    d |= (uint64_t)1 << 16;
    d |= (uint64_t)64 << 32;
    d |= (uint64_t)1 << 62;
    return d;
}

#define ACC8(a, i) "+f"(a[i]), "+f"(a[i + 1]), "+f"(a[i + 2]), "+f"(a[i + 3]), "+f"(a[i + 4]), "+f"(a[i + 5]), "+f"(a[i + 6]), "+f"(a[i + 7])

__device__ __forceinline__ void wgmma_m64n256k16(float (&d)[128], uint64_t da, uint64_t db, int scale_d) {
    asm volatile(
        "{\n"
        ".reg .pred p;\n"
        "setp.ne.b32 p, %130, 0;\n"
        "wgmma.mma_async.sync.aligned.m64n256k16.f32.bf16.bf16 "
        "{%0, %1, %2, %3, %4, %5, %6, %7, %8, %9, %10, %11, %12, %13, %14, %15, "
        "%16, %17, %18, %19, %20, %21, %22, %23, %24, %25, %26, %27, %28, %29, %30, %31, "
        "%32, %33, %34, %35, %36, %37, %38, %39, %40, %41, %42, %43, %44, %45, %46, %47, "
        "%48, %49, %50, %51, %52, %53, %54, %55, %56, %57, %58, %59, %60, %61, %62, %63, "
        "%64, %65, %66, %67, %68, %69, %70, %71, %72, %73, %74, %75, %76, %77, %78, %79, "
        "%80, %81, %82, %83, %84, %85, %86, %87, %88, %89, %90, %91, %92, %93, %94, %95, "
        "%96, %97, %98, %99, %100, %101, %102, %103, %104, %105, %106, %107, %108, %109, %110, %111, "
        "%112, %113, %114, %115, %116, %117, %118, %119, %120, %121, %122, %123, %124, %125, %126, %127}, "
        "%128, %129, p, 1, 1, 0, 0;\n"
        "}\n"
        : ACC8(d, 0), ACC8(d, 8), ACC8(d, 16), ACC8(d, 24), ACC8(d, 32), ACC8(d, 40), ACC8(d, 48), ACC8(d, 56),
          ACC8(d, 64), ACC8(d, 72), ACC8(d, 80), ACC8(d, 88), ACC8(d, 96), ACC8(d, 104), ACC8(d, 112), ACC8(d, 120)
        : "l"(da), "l"(db), "r"(scale_d));
}

__device__ __forceinline__ void wgmma_rs_n128(float (&d)[64], uint32_t a0, uint32_t a1, uint32_t a2, uint32_t a3,
                                              uint64_t db) {
    asm volatile(
        "wgmma.mma_async.sync.aligned.m64n128k16.f32.bf16.bf16 {%0, %1, %2, %3, %4, %5, %6, %7, %8, %9, %10, %11, %12, %13, %14, %15, %16, %17, %18, %19, %20, %21, %22, %23, %24, %25, %26, %27, %28, %29, %30, %31, %32, %33, %34, %35, %36, %37, %38, %39, %40, %41, %42, %43, %44, %45, %46, %47, %48, %49, %50, %51, %52, %53, %54, %55, %56, %57, %58, %59, %60, %61, %62, %63}, {%64, %65, %66, %67}, %68, 1, 1, 1, 0;\n"
        : "+f"(d[0]), "+f"(d[1]), "+f"(d[2]), "+f"(d[3]), "+f"(d[4]), "+f"(d[5]), "+f"(d[6]), "+f"(d[7]), "+f"(d[8]), "+f"(d[9]), "+f"(d[10]), "+f"(d[11]), "+f"(d[12]), "+f"(d[13]), "+f"(d[14]), "+f"(d[15]), "+f"(d[16]), "+f"(d[17]), "+f"(d[18]), "+f"(d[19]), "+f"(d[20]), "+f"(d[21]), "+f"(d[22]), "+f"(d[23]), "+f"(d[24]), "+f"(d[25]), "+f"(d[26]), "+f"(d[27]), "+f"(d[28]), "+f"(d[29]), "+f"(d[30]), "+f"(d[31]), "+f"(d[32]), "+f"(d[33]), "+f"(d[34]), "+f"(d[35]), "+f"(d[36]), "+f"(d[37]), "+f"(d[38]), "+f"(d[39]), "+f"(d[40]), "+f"(d[41]), "+f"(d[42]), "+f"(d[43]), "+f"(d[44]), "+f"(d[45]), "+f"(d[46]), "+f"(d[47]), "+f"(d[48]), "+f"(d[49]), "+f"(d[50]), "+f"(d[51]), "+f"(d[52]), "+f"(d[53]), "+f"(d[54]), "+f"(d[55]), "+f"(d[56]), "+f"(d[57]), "+f"(d[58]), "+f"(d[59]), "+f"(d[60]), "+f"(d[61]), "+f"(d[62]), "+f"(d[63])
        : "r"(a0), "r"(a1), "r"(a2), "r"(a3), "l"(db));
}
__device__ __forceinline__ void wgmma_rs_n96(float (&d)[64], uint32_t a0, uint32_t a1, uint32_t a2, uint32_t a3,
                                              uint64_t db) {
    asm volatile(
        "wgmma.mma_async.sync.aligned.m64n96k16.f32.bf16.bf16 {%0, %1, %2, %3, %4, %5, %6, %7, %8, %9, %10, %11, %12, %13, %14, %15, %16, %17, %18, %19, %20, %21, %22, %23, %24, %25, %26, %27, %28, %29, %30, %31, %32, %33, %34, %35, %36, %37, %38, %39, %40, %41, %42, %43, %44, %45, %46, %47}, {%48, %49, %50, %51}, %52, 1, 1, 1, 0;\n"
        : "+f"(d[16]), "+f"(d[17]), "+f"(d[18]), "+f"(d[19]), "+f"(d[20]), "+f"(d[21]), "+f"(d[22]), "+f"(d[23]), "+f"(d[24]), "+f"(d[25]), "+f"(d[26]), "+f"(d[27]), "+f"(d[28]), "+f"(d[29]), "+f"(d[30]), "+f"(d[31]), "+f"(d[32]), "+f"(d[33]), "+f"(d[34]), "+f"(d[35]), "+f"(d[36]), "+f"(d[37]), "+f"(d[38]), "+f"(d[39]), "+f"(d[40]), "+f"(d[41]), "+f"(d[42]), "+f"(d[43]), "+f"(d[44]), "+f"(d[45]), "+f"(d[46]), "+f"(d[47]), "+f"(d[48]), "+f"(d[49]), "+f"(d[50]), "+f"(d[51]), "+f"(d[52]), "+f"(d[53]), "+f"(d[54]), "+f"(d[55]), "+f"(d[56]), "+f"(d[57]), "+f"(d[58]), "+f"(d[59]), "+f"(d[60]), "+f"(d[61]), "+f"(d[62]), "+f"(d[63])
        : "r"(a0), "r"(a1), "r"(a2), "r"(a3), "l"(db));
}
__device__ __forceinline__ void wgmma_rs_n64(float (&d)[64], uint32_t a0, uint32_t a1, uint32_t a2, uint32_t a3,
                                              uint64_t db) {
    asm volatile(
        "wgmma.mma_async.sync.aligned.m64n64k16.f32.bf16.bf16 {%0, %1, %2, %3, %4, %5, %6, %7, %8, %9, %10, %11, %12, %13, %14, %15, %16, %17, %18, %19, %20, %21, %22, %23, %24, %25, %26, %27, %28, %29, %30, %31}, {%32, %33, %34, %35}, %36, 1, 1, 1, 0;\n"
        : "+f"(d[32]), "+f"(d[33]), "+f"(d[34]), "+f"(d[35]), "+f"(d[36]), "+f"(d[37]), "+f"(d[38]), "+f"(d[39]), "+f"(d[40]), "+f"(d[41]), "+f"(d[42]), "+f"(d[43]), "+f"(d[44]), "+f"(d[45]), "+f"(d[46]), "+f"(d[47]), "+f"(d[48]), "+f"(d[49]), "+f"(d[50]), "+f"(d[51]), "+f"(d[52]), "+f"(d[53]), "+f"(d[54]), "+f"(d[55]), "+f"(d[56]), "+f"(d[57]), "+f"(d[58]), "+f"(d[59]), "+f"(d[60]), "+f"(d[61]), "+f"(d[62]), "+f"(d[63])
        : "r"(a0), "r"(a1), "r"(a2), "r"(a3), "l"(db));
}
__device__ __forceinline__ void wgmma_rs_n32(float (&d)[64], uint32_t a0, uint32_t a1, uint32_t a2, uint32_t a3,
                                              uint64_t db) {
    asm volatile(
        "wgmma.mma_async.sync.aligned.m64n32k16.f32.bf16.bf16 {%0, %1, %2, %3, %4, %5, %6, %7, %8, %9, %10, %11, %12, %13, %14, %15}, {%16, %17, %18, %19}, %20, 1, 1, 1, 0;\n"
        : "+f"(d[48]), "+f"(d[49]), "+f"(d[50]), "+f"(d[51]), "+f"(d[52]), "+f"(d[53]), "+f"(d[54]), "+f"(d[55]), "+f"(d[56]), "+f"(d[57]), "+f"(d[58]), "+f"(d[59]), "+f"(d[60]), "+f"(d[61]), "+f"(d[62]), "+f"(d[63])
        : "r"(a0), "r"(a1), "r"(a2), "r"(a3), "l"(db));
}

__device__ __forceinline__ void mma_bf16_16816(float (&c)[4], uint32_t a0, uint32_t a1, uint32_t a2, uint32_t a3,
                                               uint32_t b0, uint32_t b1) {
    asm volatile(
        "mma.sync.aligned.m16n8k16.row.col.f32.bf16.bf16.f32 {%0,%1,%2,%3}, {%4,%5,%6,%7}, {%8,%9}, {%0,%1,%2,%3};"
        : "+f"(c[0]), "+f"(c[1]), "+f"(c[2]), "+f"(c[3])
        : "r"(a0), "r"(a1), "r"(a2), "r"(a3), "r"(b0), "r"(b1));
}

__device__ __forceinline__ uint32_t lds32(uint32_t addr) {
    uint32_t v;
    asm volatile("ld.shared.b32 %0, [%1];" : "=r"(v) : "r"(addr));
    return v;
}
__device__ __forceinline__ uint32_t pack_bf16(float lo, float hi) {
    __nv_bfloat162 t = __floats2bfloat162_rn(lo, hi);
    return *reinterpret_cast<uint32_t*>(&t);
}
__device__ __forceinline__ float bf_lo(uint32_t v) { return __uint_as_float(v << 16); }
__device__ __forceinline__ float bf_hi(uint32_t v) { return __uint_as_float(v & 0xffff0000u); }
__device__ __forceinline__ __nv_bfloat162 u2b(uint32_t v) { return *reinterpret_cast<__nv_bfloat162*>(&v); }
__device__ __forceinline__ uint32_t b2u(__nv_bfloat162 v) { return *reinterpret_cast<uint32_t*>(&v); }
__device__ __forceinline__ float rbf(float x) { return __bfloat162float(__float2bfloat16_rn(x)); }

__device__ __forceinline__ void named_bar_sync(int id, int n) {
    asm volatile("bar.sync %0, %1;" ::"r"(id), "r"(n) : "memory");
}

constexpr int BM = 128, BN = 256, BK = 64, STAGES = 4;
constexpr int A_BYTES = BM * BK * 2;
constexpr int B_BYTES = BN * BK * 2;
constexpr int STAGE_BYTES = A_BYTES + B_BYTES;
constexpr int SMEM_BYTES = STAGES * STAGE_BYTES + 34688 + 1024;
constexpr int NTHREADS = 384;

constexpr int STG_PITCH = 528;
constexpr int STG_WG_BYTES = 64 * STG_PITCH;

constexpr int KV_PITCH = 112 + 2048 + 8;
constexpr int KV_BYTES = 8 * KV_PITCH * 2;
constexpr int REV_PITCH = 2096;
constexpr int REV_BYTES = 8 * 2 * REV_PITCH * 2;
constexpr int YS_BYTES = 2048 * 8 * 2;
constexpr int CONV_KV_OFF = STAGES * STAGE_BYTES;
constexpr int CONV_REV_OFF = 2 * STAGE_BYTES;
constexpr int STG1_OFF = 2 * STAGE_BYTES;
constexpr int CONV_YS_OFF = CONV_REV_OFF + REV_BYTES;
static_assert(CONV_REV_OFF + REV_BYTES <= STAGES * STAGE_BYTES && STG1_OFF + 2 * STG_WG_BYTES <= STAGES * STAGE_BYTES && KV_BYTES <= 34688, "conv smem");
constexpr int PL_PAD = 32;
constexpr int PLANE_BYTES = (PL_PAD + 128) * 16;
constexpr int KVP_BYTES = 2 * PLANE_BYTES;
constexpr int KVP_OFF_HI = CONV_REV_OFF + REV_BYTES;
static_assert(6 * KVP_BYTES <= 34688 && KVP_OFF_HI + 2 * KVP_BYTES <= STAGES * STAGE_BYTES, "kv planes");
constexpr int YP = 131;
static_assert(16 * YP * 4 <= 2 * REV_PITCH * 2, "Y buffer");
constexpr int REV_Y0 = 2054;

struct Params {
    const __nv_bfloat16 *q, *k, *v, *shift_k, *ssm_k, *ssm_D;
    __nv_bfloat16* out;
};

struct PipeState {
    int stage;
    uint32_t phase;
    __device__ __forceinline__ void advance() {
        if (++stage == STAGES) { stage = 0; phase ^= 1; }
    }
};

template <bool B_MC>
__device__ __forceinline__ void gemm_produce(PipeState& ps, uint32_t sbase, uint32_t full0, uint32_t empty0,
                                             const CUtensorMap* mA, const CUtensorMap* mB, int arow, int brow,
                                             int ahalf, int bhalf, uint16_t maskA, uint16_t maskB, int k0, int nk) {
#pragma unroll 1
    for (int it = k0; it < nk; ++it) {
        mbar_wait(empty0 + 8 * ps.stage, ps.phase ^ 1);
        uint32_t fb = full0 + 8 * ps.stage;
        mbar_expect_tx(fb, STAGE_BYTES);
        uint32_t sa = sbase + ps.stage * STAGE_BYTES;
        tma_load_2d(sa, mA, fb, it * BK, arow);
        tma_load_2d(sa + A_BYTES / 2, mA, fb, it * BK, arow + BM / 2);
        if (B_MC) {
            tma_load_2d_mc(sa + A_BYTES + bhalf * (B_BYTES / 2), mB, fb, it * BK, brow + bhalf * (BN / 2), maskB);
        } else {
            tma_load_2d(sa + A_BYTES, mB, fb, it * BK, brow);
            tma_load_2d(sa + A_BYTES + B_BYTES / 2, mB, fb, it * BK, brow + BN / 2);
        }
        ps.advance();
    }
}

__device__ __forceinline__ void release_stage(uint32_t empty0, uint32_t emptyA, uint32_t emptyB, int stage) {
    if ((threadIdx.x & 31) == 0) {
        mbar_arrive(empty0 + 8 * stage);
        mbar_arrive_cluster(emptyB + 8 * stage);
    }
}

__device__ __forceinline__ void gemm_consume(PipeState& ps, float (&acc)[128], uint32_t sbase, uint32_t full0,
                                             uint32_t empty0, uint32_t emptyA, uint32_t emptyB, int wg, int nk,
                                             int n_hold) {
    int prev_stage = -1;
#pragma unroll 1
    for (int it = 0; it < nk; ++it) {
        mbar_wait(full0 + 8 * ps.stage, ps.phase);
        uint32_t sa = sbase + ps.stage * STAGE_BYTES + wg * (64 * 128);
        uint32_t sb = sbase + ps.stage * STAGE_BYTES + A_BYTES;
        uint64_t da = make_desc_sw128(sa);
        uint64_t db = make_desc_sw128(sb);
        wgmma_fence();
#pragma unroll
        for (int kk = 0; kk < 4; ++kk) {
            wgmma_m64n256k16(acc, da + (uint64_t)(kk * 2), db + (uint64_t)(kk * 2), (it > 0 || kk > 0) ? 1 : 0);
        }
        wgmma_commit();
        if (prev_stage >= 0) {
            wgmma_wait<1>();
            if (it - 1 < nk - n_hold) release_stage(empty0, emptyA, emptyB, prev_stage);
        }
        prev_stage = ps.stage;
        ps.advance();
    }
    wgmma_wait<0>();
    if (n_hold == 0) release_stage(empty0, emptyA, emptyB, prev_stage);
}

__device__ __forceinline__ void store_tile_bf16(const uint32_t (&pk)[64], uint8_t* stg, __nv_bfloat16* gdst, int ld,
                                                int wg_tid, int bar_id) {
    const int warp = wg_tid >> 5, lane = wg_tid & 31;
    const int r0 = warp * 16 + (lane >> 2);
    const int c0 = (lane & 3) * 2;
#pragma unroll
    for (int j = 0; j < 32; ++j) {
        *reinterpret_cast<uint32_t*>(stg + r0 * STG_PITCH + (j * 8 + c0) * 2) = pk[2 * j];
        *reinterpret_cast<uint32_t*>(stg + (r0 + 8) * STG_PITCH + (j * 8 + c0) * 2) = pk[2 * j + 1];
    }
    named_bar_sync(bar_id, 128);
#pragma unroll
    for (int p = 0; p < 16; ++p) {
        int r = p * 4 + (wg_tid >> 5);
        int cb = (wg_tid & 31) * 16;
        uint4 val = *reinterpret_cast<const uint4*>(stg + r * STG_PITCH + cb);
        *reinterpret_cast<uint4*>(reinterpret_cast<uint8_t*>(gdst + (size_t)r * ld) + cb) = val;
    }
}

__device__ __forceinline__ void counter_wait(unsigned int* ready, unsigned int* passed, unsigned int n_ready,
                                             unsigned int n_wait) {
    unsigned int v;
    long long spins = 0;
    do {
        asm volatile("ld.acquire.gpu.global.u32 %0, [%1];" : "=r"(v) : "l"(ready) : "memory");
    } while (v < n_ready && ++spins < (1ll << 26));
    unsigned int old = atomicAdd(passed, 1u);
    if (old == n_wait - 1) {
        *passed = 0;
        *ready = 0;
        __threadfence();
    }
}

__device__ __forceinline__ void kv_prepass(const Params& p, int s0, int ctid) {
    const int c0 = ctid * 4;
    uint2 kr[19], vr[16];
#pragma unroll
    for (int j = 0; j < 19; ++j) {
        int s = s0 - 3 + j;
        if (s >= 0) kr[j] = __ldg(reinterpret_cast<const uint2*>(p.k + (size_t)s * D_DIM + c0));
        else kr[j] = make_uint2(0, 0);
    }
#pragma unroll
    for (int j = 0; j < 16; ++j) vr[j] = __ldg(reinterpret_cast<const uint2*>(p.v + (size_t)(s0 + j) * D_DIM + c0));
    uint4 w0 = __ldg(reinterpret_cast<const uint4*>(p.shift_k + (size_t)c0 * 4));
    uint4 w1 = __ldg(reinterpret_cast<const uint4*>(p.shift_k + (size_t)c0 * 4 + 8));
    uint32_t wt[2][4];
    wt[0][0] = __byte_perm(w0.x, w0.z, 0x5410); wt[0][1] = __byte_perm(w0.x, w0.z, 0x7632);
    wt[0][2] = __byte_perm(w0.y, w0.w, 0x5410); wt[0][3] = __byte_perm(w0.y, w0.w, 0x7632);
    wt[1][0] = __byte_perm(w1.x, w1.z, 0x5410); wt[1][1] = __byte_perm(w1.x, w1.z, 0x7632);
    wt[1][2] = __byte_perm(w1.y, w1.w, 0x5410); wt[1][3] = __byte_perm(w1.y, w1.w, 0x7632);
#pragma unroll
    for (int pr = 0; pr < 2; ++pr) {
        uint32_t r[16];
#pragma unroll
        for (int j = 0; j < 16; ++j) {
            __nv_bfloat162 k0 = u2b(pr ? kr[j].y : kr[j].x), k1 = u2b(pr ? kr[j + 1].y : kr[j + 1].x);
            __nv_bfloat162 k2 = u2b(pr ? kr[j + 2].y : kr[j + 2].x), k3 = u2b(pr ? kr[j + 3].y : kr[j + 3].x);
            __nv_bfloat162 acc = __hmul2(k0, u2b(wt[pr][3]));
            acc = __hadd2(acc, __hmul2(k1, u2b(wt[pr][2])));
            acc = __hadd2(acc, __hmul2(k2, u2b(wt[pr][1])));
            acc = __hadd2(acc, __hmul2(k3, u2b(wt[pr][0])));
            acc = __hmul2(acc, u2b(pr ? vr[j].y : vr[j].x));
            r[j] = b2u(acc);
        }
        uint32_t lo[8], hi[8];
#pragma unroll
        for (int j = 0; j < 8; ++j) {
            lo[j] = __byte_perm(r[2 * j], r[2 * j + 1], 0x5410);
            hi[j] = __byte_perm(r[2 * j], r[2 * j + 1], 0x7632);
        }
        uint4* d0 = reinterpret_cast<uint4*>(g_kvT + (size_t)(c0 + 2 * pr) * S_LEN + s0);
        uint4* d1 = reinterpret_cast<uint4*>(g_kvT + (size_t)(c0 + 2 * pr + 1) * S_LEN + s0);
        d0[0] = make_uint4(lo[0], lo[1], lo[2], lo[3]);
        d0[1] = make_uint4(lo[4], lo[5], lo[6], lo[7]);
        d1[0] = make_uint4(hi[0], hi[1], hi[2], hi[3]);
        d1[1] = make_uint4(hi[4], hi[5], hi[6], hi[7]);
    }
}

__device__ __forceinline__ void out_postpass(const Params& p, int s0, int ctid) {
    const int c0 = ctid * 4;
    uint2 qr[16];
#pragma unroll
    for (int j = 0; j < 16; ++j) qr[j] = __ldg(reinterpret_cast<const uint2*>(p.q + (size_t)(s0 + j) * D_DIM + c0));
    uint4 yy[4][2];
#pragma unroll
    for (int c = 0; c < 4; ++c) {
        const uint4* src = reinterpret_cast<const uint4*>(g_yT + (size_t)(c0 + c) * S_LEN + s0);
        yy[c][0] = __ldcg(src);
        yy[c][1] = __ldcg(src + 1);
    }
#pragma unroll
    for (int j = 0; j < 16; j += 2) {
        uint32_t y0 = reinterpret_cast<const uint32_t*>(&yy[0][0])[j >> 1], y1 = reinterpret_cast<const uint32_t*>(&yy[1][0])[j >> 1];
        uint32_t y2 = reinterpret_cast<const uint32_t*>(&yy[2][0])[j >> 1], y3 = reinterpret_cast<const uint32_t*>(&yy[3][0])[j >> 1];
        uint2 o;
        o.x = b2u(__hmul2(u2b(qr[j].x), u2b(__byte_perm(y0, y1, 0x5410))));
        o.y = b2u(__hmul2(u2b(qr[j].y), u2b(__byte_perm(y2, y3, 0x5410))));
        *reinterpret_cast<uint2*>(p.out + (size_t)(s0 + j) * 2048 + 1024 + c0) = o;
        o.x = b2u(__hmul2(u2b(qr[j + 1].x), u2b(__byte_perm(y0, y1, 0x7632))));
        o.y = b2u(__hmul2(u2b(qr[j + 1].y), u2b(__byte_perm(y2, y3, 0x7632))));
        *reinterpret_cast<uint2*>(p.out + (size_t)(s0 + j + 1) * 2048 + 1024 + c0) = o;
    }
}

__device__ __forceinline__ void conv_phase(const Params& p, uint8_t* smem, int ch0, int ctid, const uint4 (&hv)[8], const uint4 (&t)[8]) {
    const int warp = ctid >> 5, lane = ctid & 31;
    __nv_bfloat16* kvs = reinterpret_cast<__nv_bfloat16*>(smem + CONV_KV_OFF) + (size_t)warp * KV_PITCH;
    __nv_bfloat16* rev = reinterpret_cast<__nv_bfloat16*>(smem + CONV_REV_OFF);

    {
        __nv_bfloat16* r0 = rev + (size_t)(warp * 2) * REV_PITCH;
        __nv_bfloat16* r1 = r0 + REV_PITCH;
        const unsigned short* hraw = reinterpret_cast<const unsigned short*>(p.ssm_k + (size_t)(ch0 + warp) * S_LEN);
#pragma unroll
        for (int it = 0; it < 8; ++it) {
            int idx = 8 * (lane + 32 * it);
            uint32_t prev = (idx > 0) ? (uint32_t)__ldg(hraw + idx - 1) : 0u;
            uint4 h4 = hv[it];
            uint4 o1, o0;
            o1.x = __byte_perm(h4.w, 0, 0x1032); o1.y = __byte_perm(h4.z, 0, 0x1032);
            o1.z = __byte_perm(h4.y, 0, 0x1032); o1.w = __byte_perm(h4.x, 0, 0x1032);
            *reinterpret_cast<uint4*>(r1 + (REV_Y0 - 6 - idx)) = o1;
            o0.x = __byte_perm(h4.w, h4.z, 0x7610);
            o0.y = __byte_perm(h4.z, h4.y, 0x7610);
            o0.z = __byte_perm(h4.y, h4.x, 0x7610);
            o0.w = __byte_perm(h4.x, prev, 0x5410);
            *reinterpret_cast<uint4*>(r0 + (REV_Y0 - 6 - idx)) = o0;
        }
        if (lane == 31) r0[REV_Y0 - 2047] = reinterpret_cast<const __nv_bfloat16*>(&hv[7])[7];
        if (lane < 24) {
            int idx = -1 - lane;
            r0[REV_Y0 - idx] = __float2bfloat16_rn(0.f);
            r1[REV_Y0 + 1 - idx] = __float2bfloat16_rn(0.f);
        }
    }
    {
        uint8_t* kp = smem + ((warp < 6) ? (CONV_KV_OFF + warp * KVP_BYTES) : (KVP_OFF_HI + (warp - 6) * KVP_BYTES));
#pragma unroll
        for (int it = 0; it < 8; ++it) {
            int c = lane + 32 * it;
            *reinterpret_cast<uint4*>(kp + (c & 1) * PLANE_BYTES + (PL_PAD + (c >> 1)) * 16) = t[it];
        }
        *reinterpret_cast<uint4*>(kp + lane * 16) = make_uint4(0, 0, 0, 0);
        *reinterpret_cast<uint4*>(kp + PLANE_BYTES + lane * 16) = make_uint4(0, 0, 0, 0);
    }
    asm volatile("fence.proxy.async.shared::cta;" ::: "memory");
    const int wg = ctid >> 7, w4 = warp & 3, wtid = ctid & 127;
    named_bar_sync(3 + wg, 128);
    TSTAMP(6);
    const int g = lane >> 2, c2 = (lane & 3) * 2;
#pragma unroll 1
    for (int cc = 0; cc < 4; ++cc) {
        const int ch = wg * 4 + cc;
        const uint32_t kp = smem_u32(smem) + (uint32_t)((ch < 6) ? (CONV_KV_OFF + ch * KVP_BYTES) : (KVP_OFF_HI + (ch - 6) * KVP_BYTES));
        const uint32_t rev_base = smem_u32(rev + (size_t)(ch * 2 + (g & 1)) * REV_PITCH) +
                                  2u * (uint32_t)(REV_Y0 + (g & 1) - g + c2 - 16 * w4);
        float acc[64];
#pragma unroll
        for (int i = 0; i < 64; ++i) acc[i] = 0.f;
        const uint64_t dbase = ((uint64_t)(PLANE_BYTES >> 4) << 16) | ((uint64_t)(128 >> 4) << 32);
#pragma unroll
        for (int qd = 0; qd < 4; ++qd) {
            uint32_t f[8][3];
#pragma unroll
            for (int st = 0; st < 8; ++st) {
                int delta = 16 * (32 * qd + 4 * st);
                f[st][0] = lds32(rev_base - 2u * (uint32_t)(delta - 8));
                f[st][1] = lds32(rev_base - 2u * (uint32_t)(delta));
                f[st][2] = lds32(rev_base - 2u * (uint32_t)(delta + 8));
            }
            wgmma_fence();
#pragma unroll
            for (int st = 0; st < 8; ++st) {
                uint32_t baddr = kp + (uint32_t)((PL_PAD - 4 * st) * 16);
                uint64_t db = dbase | (uint64_t)((baddr & 0x3FFFF) >> 4);
                if (qd == 0) wgmma_rs_n128(acc, f[st][1], f[st][2], f[st][0], f[st][1], db);
                else if (qd == 1) wgmma_rs_n96(acc, f[st][1], f[st][2], f[st][0], f[st][1], db);
                else if (qd == 2) wgmma_rs_n64(acc, f[st][1], f[st][2], f[st][0], f[st][1], db);
                else wgmma_rs_n32(acc, f[st][1], f[st][2], f[st][0], f[st][1], db);
            }
            wgmma_commit();
            if (qd & 1) wgmma_wait<0>();
        }
        float* Yb = reinterpret_cast<float*>(smem + wg * (4 * 16 * YP * 4));
        float* Yw = Yb + w4 * (16 * YP);
        named_bar_sync(3 + wg, 128);
        if (lane < 16) { Yw[lane * YP + 0] = 0.f; Yw[lane * YP + 1] = 0.f; Yw[lane * YP + 2] = 0.f; }
        __syncwarp();
#pragma unroll
        for (int j = 0; j < 16; ++j) {
#pragma unroll
            for (int e = 0; e < 4; ++e) {
                int col = 8 * j + c2 + (e & 1) + w4;
                int row = g + 8 * (e >> 1);
                Yw[row * YP + col] = acc[4 * j + e];
            }
        }
        named_bar_sync(3 + wg, 128);
        {
            const __nv_bfloat162 D2 = __bfloat162bfloat162(p.ssm_D[ch0 + ch]);
#pragma unroll
            for (int it = 0; it < 2; ++it) {
                int c = wtid + 128 * it;
                int n = c >> 1, hh = c & 1;
                uint4 kv4;
                asm volatile("ld.shared.v4.b32 {%0,%1,%2,%3}, [%4];" : "=r"(kv4.x), "=r"(kv4.y), "=r"(kv4.z), "=r"(kv4.w)
                             : "r"(kp + (uint32_t)(hh * PLANE_BYTES + (PL_PAD + n) * 16)));
                const uint32_t* kvw = reinterpret_cast<const uint32_t*>(&kv4);
                uint32_t o[4];
#pragma unroll
                for (int e = 0; e < 4; ++e) {
                    const float* yp = Yb + (8 * hh + 2 * e) * YP + n;
                    float y0 = (yp[0] + yp[16 * YP]) + (yp[32 * YP] + yp[48 * YP]);
                    float y1 = (yp[YP] + yp[17 * YP]) + (yp[33 * YP] + yp[49 * YP]);
                    __nv_bfloat162 yb = __floats2bfloat162_rn(y0, y1);
                    o[e] = b2u(__hadd2(yb, __hmul2(u2b(kvw[e]), D2)));
                }
                *reinterpret_cast<uint4*>(g_yT + (size_t)(ch0 + ch) * S_LEN + 8 * c) = make_uint4(o[0], o[1], o[2], o[3]);
            }
        }
    }
    TSTAMP(7);
}

__global__ void __cluster_dims__(2, 1, 1) __launch_bounds__(NTHREADS, 1)
fused_kernel(const __grid_constant__ CUtensorMap mWre, const __grid_constant__ CUtensorMap mWim,
             const __grid_constant__ CUtensorMap mX, const __grid_constant__ CUtensorMap mAB,
             const __grid_constant__ CUtensorMap mCr, const __grid_constant__ CUtensorMap mCi,
             const Params p) {
    extern __shared__ uint8_t smem_raw[];
    __shared__ __align__(8) uint64_t bars[2 * STAGES];
    uint8_t* smem = smem_raw + ((1024u - (smem_u32(smem_raw) & 1023u)) & 1023u);
    const uint32_t sbase = smem_u32(smem);
    const uint32_t full0 = smem_u32(&bars[0]);
    const uint32_t empty0 = smem_u32(&bars[STAGES]);
    const int tid = threadIdx.x;
    const int wgid = tid >> 7;
    const int bid = blockIdx.x;

    if (tid == 0) {
        for (int i = 0; i < STAGES; ++i) {
            mbar_init(full0 + 8 * i, 1);
            mbar_init(empty0 + 8 * i, 16);
        }
        asm volatile("fence.mbarrier_init.release.cluster;" ::: "memory");
    }
    __syncthreads();
    cluster_sync_all();

    const int rank = bid & 1, pair = bid >> 1;
    const int g1_m = 2 * (pair >> 3) + rank, g1_n = pair & 7;
    const int part = rank;
    const int g2_m = pair >> 2, g2_n = pair & 3;
    const int grp = part * 4 + g2_n;

    if (wgid == 0) {
        if (tid == 0) {
            PipeState ps{0, 0};
            const CUtensorMap* mW = (g1_m < 8) ? &mWre : &mWim;
            gemm_produce<true>(ps, sbase, full0, empty0, mW, &mX, (g1_m & 7) * BM, g1_n * BN, 0, rank, 0, 3, 0, D_DIM / BK);
        }
        if (tid >= 32) {
#pragma unroll 1
            for (int t = tid - 32; t < 256; t += 96) { kv_prepass(p, bid * 16, t); TSTAMP2(8 + t / 96); }
            named_bar_sync(5, 96);
            TSTAMP2(11);
            if (tid == 32) asm volatile("red.release.gpu.global.add.u32 [%0], 1;" ::"l"(&g_sync[0]) : "memory");
            if (tid < 64) {
                __syncwarp();
                named_bar_sync(6, 288);
                if (tid == 32) {
                    asm volatile("fence.proxy.async;" ::: "memory");
                    asm volatile("red.release.gpu.global.add.u32 [%0], 1;" ::"l"(&g_ready[g1_m >> 1]) : "memory");
                }
             }
        }
        const CUtensorMap* mC = part ? &mCi : &mCr;
        PipeState ps2{0, 0};
        if (tid == 0) {
            counter_wait(&g_ready[grp], &g_passed[grp], 16u, 16u);
            asm volatile("fence.proxy.async;" ::: "memory");
#pragma unroll 1
            for (int it = g2_n * 8; it < g2_n * 8 + 8; ++it) {
                asm volatile("cp.async.bulk.prefetch.tensor.2d.L2.global [%0, {%1, %2}];" ::"l"((uint64_t)mC),
                             "r"(it * BK), "r"(g2_m * BM) : "memory");
                asm volatile("cp.async.bulk.prefetch.tensor.2d.L2.global [%0, {%1, %2}];" ::"l"((uint64_t)mC),
                             "r"(it * BK), "r"(g2_m * BM + 64) : "memory");
            }
        }
        if (tid == 0) {
            gemm_produce<false>(ps2, sbase, full0, empty0, mC, &mAB, g2_m * BM, grp * BN, 0, 0, 0, 0, 0, S_LEN / BK);
        }
        if (tid >= 32) {
            if (tid == 32) counter_wait(&g_sync[2], &g_sync[3], 128u, 128u);
            named_bar_sync(5, 96);
#pragma unroll 1
            for (int t = tid - 32; t < 256; t += 96) out_postpass(p, bid * 16, t);
        }
        __syncwarp();
        asm volatile("barrier.cluster.arrive.release.aligned;\n barrier.cluster.wait.acquire.aligned;" ::: "memory");
        asm volatile("barrier.cluster.arrive.release.aligned;\n barrier.cluster.wait.acquire.aligned;" ::: "memory");
    } else {
        const int wg = wgid - 1;
        const int ctid = tid - 128;
        const int wtid = tid & 127;
        PipeState ps{0, 0};
        float acc[128];
        const uint32_t emptyA = 0, emptyB = mapa_u32(empty0, rank ^ 1);
        TSTAMP(0);
        gemm_consume(ps, acc, sbase, full0, empty0, emptyA, emptyB, wg, D_DIM / BK, 4);
        named_bar_sync(1, 256);
        TSTAMP(1);
        uint4 hv[8], kvr[8];
        {
            uint32_t pk[64];
#pragma unroll
            for (int i = 0; i < 64; ++i) pk[i] = pack_bf16(acc[2 * i], acc[2 * i + 1]);
            if (ctid == 0) counter_wait(&g_sync[0], &g_sync[1], 128u, 128u);
            named_bar_sync(1, 256);
            {
                const int cw = ctid >> 5, cl = ctid & 31;
                const uint4* hs = reinterpret_cast<const uint4*>(p.ssm_k + (size_t)(bid * 8 + cw) * S_LEN);
                const uint4* ks = reinterpret_cast<const uint4*>(g_kvT + (size_t)(bid * 8 + cw) * S_LEN);
#pragma unroll
                for (int it = 0; it < 8; ++it) { hv[it] = __ldg(hs + cl + 32 * it); kvr[it] = __ldcg(ks + cl + 32 * it); }
            }
            __nv_bfloat16* dst = g_abT + (size_t)(g1_m * BM + wg * 64) * 2048 + g1_n * BN;
            store_tile_bf16(pk, smem + STG1_OFF + wg * STG_WG_BYTES, dst, 2048, wtid, 3 + wg);
        }
        asm volatile("bar.arrive 6, 288;" ::: "memory");
        TSTAMP(2);
        named_bar_sync(1, 256);
        conv_phase(p, smem, bid * 8, ctid, hv, kvr);
        asm volatile("fence.proxy.async.shared::cta;" ::: "memory");
        __syncwarp();
        release_stage(empty0, emptyA, emptyB, 0);
        release_stage(empty0, emptyA, emptyB, 1);
        release_stage(empty0, emptyA, emptyB, 2);
        release_stage(empty0, emptyA, emptyB, 3);
        named_bar_sync(1, 256);
        if (ctid == 0) asm volatile("red.release.gpu.global.add.u32 [%0], 1;" ::"l"(&g_sync[2]) : "memory");
        TSTAMP(3);
#pragma unroll
        for (int i = 0; i < 128; ++i) acc[i] = 0.f;
        gemm_consume(ps, acc, sbase, full0, empty0, emptyA, emptyB, wg, S_LEN / BK, 0);
        named_bar_sync(1, 256);
        TSTAMP(4);
        asm volatile("barrier.cluster.arrive.release.aligned;\n barrier.cluster.wait.acquire.aligned;" ::: "memory");
        uint32_t pk[64];
#pragma unroll
        for (int i = 0; i < 64; ++i) pk[i] = pack_bf16(acc[2 * i], acc[2 * i + 1]);
        const uint32_t xbuf = sbase + 2 * STG_WG_BYTES + 1024;
        const bool sender = (wg != part);
        if (sender) {
            uint32_t remote;
            remote = mapa_u32(xbuf, rank ^ 1);
#pragma unroll
            for (int i = 0; i < 64; ++i) {
                asm volatile("st.shared::cluster.b32 [%0], %1;" ::"r"(remote + (uint32_t)(i * 512 + wtid * 4)), "r"(pk[i]) : "memory");
            }
        }
        asm volatile("barrier.cluster.arrive.release.aligned;\n barrier.cluster.wait.acquire.aligned;" ::: "memory");
        if (!sender) {
#pragma unroll
            for (int i = 0; i < 64; ++i) {
                uint32_t o = lds32(xbuf + (uint32_t)(i * 512 + wtid * 4));
                uint32_t re = part ? o : pk[i];
                uint32_t im = part ? pk[i] : o;
                pk[i] = pack_bf16(bf_lo(re) - bf_lo(im), bf_hi(re) - bf_hi(im));
            }
            __nv_bfloat16* dst = p.out + (size_t)(g2_m * BM + wg * 64) * 2048 + g2_n * BN;
            store_tile_bf16(pk, smem + wg * STG_WG_BYTES, dst, 2048, wtid, 3 + wg);
        }
        TSTAMP(5);
    }
}

typedef CUresult (*PFN_encodeTiled)(CUtensorMap*, CUtensorMapDataType, cuuint32_t, void*, const cuuint64_t*,
                                    const cuuint64_t*, const cuuint32_t*, const cuuint32_t*, CUtensorMapInterleave,
                                    CUtensorMapSwizzle, CUtensorMapL2promotion, CUtensorMapFloatOOBfill);

static void make_map(PFN_encodeTiled enc, CUtensorMap* m, const void* ptr, int rows, int cols, int box_rows) {
    cuuint64_t gdim[2] = {(cuuint64_t)cols, (cuuint64_t)rows};
    cuuint64_t gstr[1] = {(cuuint64_t)cols * 2};
    cuuint32_t box[2] = {64, (cuuint32_t)box_rows};
    cuuint32_t estr[2] = {1, 1};
    enc(m, CU_TENSOR_MAP_DATA_TYPE_BFLOAT16, 2, const_cast<void*>(ptr), gdim, gstr, box, estr,
        CU_TENSOR_MAP_INTERLEAVE_NONE, CU_TENSOR_MAP_SWIZZLE_128B, CU_TENSOR_MAP_L2_PROMOTION_L2_256B,
        CU_TENSOR_MAP_FLOAT_OOB_FILL_NONE);
}

extern "C" void kernel_launch(void* const* d_in, const int* in_sizes, int n_in, void* d_out, int out_size) {
    static PFN_encodeTiled enc = nullptr;
    static bool attr_set = false;
    if (!enc) {
        void* fn = nullptr;
        cudaDriverEntryPointQueryResult qres;
        cudaGetDriverEntryPoint("cuTensorMapEncodeTiled", &fn, cudaEnableDefault, &qres);
        enc = (PFN_encodeTiled)fn;
    }
    if (!attr_set) {
        cudaFuncSetAttribute(fused_kernel, cudaFuncAttributeMaxDynamicSharedMemorySize, SMEM_BYTES);
        attr_set = true;
    }
    void* abT = nullptr;
    cudaGetSymbolAddress(&abT, g_abT);

    CUtensorMap mWre, mWim, mX, mAB, mCr, mCi;
    make_map(enc, &mX, d_in[0], 2048, 1024, BN / 2);
    make_map(enc, &mCr, d_in[1], 2048, 2048, BM / 2);
    make_map(enc, &mCi, d_in[2], 2048, 2048, BM / 2);
    make_map(enc, &mWre, d_in[3], 1024, 1024, BM / 2);
    make_map(enc, &mWim, d_in[4], 1024, 1024, BM / 2);
    make_map(enc, &mAB, abT, 2048, 2048, BN / 2);

    Params p;
    p.q = (const __nv_bfloat16*)d_in[5];
    p.k = (const __nv_bfloat16*)d_in[6];
    p.v = (const __nv_bfloat16*)d_in[7];
    p.shift_k = (const __nv_bfloat16*)d_in[8];
    p.ssm_k = (const __nv_bfloat16*)d_in[9];
    p.ssm_D = (const __nv_bfloat16*)d_in[10];
    p.out = (__nv_bfloat16*)d_out;

    fused_kernel<<<128, NTHREADS, SMEM_BYTES>>>(mWre, mWim, mX, mAB, mCr, mCi, p);
}
```

```cpp
#include <cuda_runtime.h>
#include <cuda_bf16.h>
#include <cuda.h>
#include <stdint.h>

#define S_LEN 2048
#define D_DIM 1024

__device__ __nv_bfloat16 g_abT[2048 * 2048];
__device__ unsigned int g_ready[8];
__device__ unsigned int g_passed[8];
__device__ __nv_bfloat16 g_kvT[1024 * 2048];
__device__ __nv_bfloat16 g_yT[1024 * 2048];
__device__ unsigned int g_sync[4];
#define TSTAMP(i)
#define TSTAMP2(i)

__device__ __forceinline__ uint32_t smem_u32(const void* p) {
    return (uint32_t)__cvta_generic_to_shared(p);
}
__device__ __forceinline__ void mbar_init(uint32_t bar, uint32_t count) {
    asm volatile("mbarrier.init.shared::cta.b64 [%0], %1;" ::"r"(bar), "r"(count));
}
__device__ __forceinline__ void mbar_expect_tx(uint32_t bar, uint32_t bytes) {
    asm volatile("mbarrier.arrive.expect_tx.shared::cta.b64 _, [%0], %1;" ::"r"(bar), "r"(bytes) : "memory");
}
__device__ __forceinline__ void mbar_arrive(uint32_t bar) {
    asm volatile("mbarrier.arrive.shared::cta.b64 _, [%0];" ::"r"(bar) : "memory");
}
__device__ __forceinline__ void mbar_wait(uint32_t bar, uint32_t parity) {
    asm volatile(
        "{\n"
        ".reg .pred p;\n"
        "LAB_WAIT:\n"
        "mbarrier.try_wait.parity.shared::cta.b64 p, [%0], %1;\n"
        "@p bra DONE;\n"
        "bra LAB_WAIT;\n"
        "DONE:\n"
        "}\n" ::"r"(bar), "r"(parity) : "memory");
}
__device__ __forceinline__ void tma_load_2d(uint32_t dst, const CUtensorMap* map, uint32_t bar, int c0, int c1) {
    asm volatile(
        "cp.async.bulk.tensor.2d.shared::cluster.global.mbarrier::complete_tx::bytes [%0], [%1, {%3, %4}], [%2];"
        ::"r"(dst), "l"((uint64_t)map), "r"(bar), "r"(c0), "r"(c1) : "memory");
}
__device__ __forceinline__ void tma_load_2d_mc(uint32_t dst, const CUtensorMap* map, uint32_t bar, int c0, int c1,
                                               uint16_t mask) {
    asm volatile(
        "cp.async.bulk.tensor.2d.shared::cluster.global.mbarrier::complete_tx::bytes.multicast::cluster "
        "[%0], [%1, {%3, %4}], [%2], %5;"
        ::"r"(dst), "l"((uint64_t)map), "r"(bar), "r"(c0), "r"(c1), "h"(mask) : "memory");
}
__device__ __forceinline__ uint32_t mapa_u32(uint32_t addr, uint32_t rank) {
    uint32_t r;
    asm volatile("mapa.shared::cluster.u32 %0, %1, %2;" : "=r"(r) : "r"(addr), "r"(rank));
    return r;
}
__device__ __forceinline__ void mbar_arrive_cluster(uint32_t remote_bar) {
    asm volatile("mbarrier.arrive.shared::cluster.b64 _, [%0];" ::"r"(remote_bar) : "memory");
}
__device__ __forceinline__ void cluster_sync_all() {
    asm volatile("barrier.cluster.arrive.release.aligned;\n barrier.cluster.wait.acquire.aligned;" ::: "memory");
}
__device__ __forceinline__ void wgmma_fence() { asm volatile("wgmma.fence.sync.aligned;" ::: "memory"); }
__device__ __forceinline__ void wgmma_commit() { asm volatile("wgmma.commit_group.sync.aligned;" ::: "memory"); }
template <int N>
__device__ __forceinline__ void wgmma_wait() { asm volatile("wgmma.wait_group.sync.aligned %0;" ::"n"(N) : "memory"); }

__device__ __forceinline__ uint64_t make_desc_sw128(uint32_t saddr) {
    uint64_t d = 0;
    d |= (uint64_t)((saddr & 0x3FFFF) >> 4);
    d |= (uint64_t)1 << 16;
    d |= (uint64_t)64 << 32;
    d |= (uint64_t)1 << 62;
    return d;
}

#define ACC8(a, i) "+f"(a[i]), "+f"(a[i + 1]), "+f"(a[i + 2]), "+f"(a[i + 3]), "+f"(a[i + 4]), "+f"(a[i + 5]), "+f"(a[i + 6]), "+f"(a[i + 7])

__device__ __forceinline__ void wgmma_m64n256k16(float (&d)[128], uint64_t da, uint64_t db, int scale_d) {
    asm volatile(
        "{\n"
        ".reg .pred p;\n"
        "setp.ne.b32 p, %130, 0;\n"
        "wgmma.mma_async.sync.aligned.m64n256k16.f32.bf16.bf16 "
        "{%0, %1, %2, %3, %4, %5, %6, %7, %8, %9, %10, %11, %12, %13, %14, %15, "
        "%16, %17, %18, %19, %20, %21, %22, %23, %24, %25, %26, %27, %28, %29, %30, %31, "
        "%32, %33, %34, %35, %36, %37, %38, %39, %40, %41, %42, %43, %44, %45, %46, %47, "
        "%48, %49, %50, %51, %52, %53, %54, %55, %56, %57, %58, %59, %60, %61, %62, %63, "
        "%64, %65, %66, %67, %68, %69, %70, %71, %72, %73, %74, %75, %76, %77, %78, %79, "
        "%80, %81, %82, %83, %84, %85, %86, %87, %88, %89, %90, %91, %92, %93, %94, %95, "
        "%96, %97, %98, %99, %100, %101, %102, %103, %104, %105, %106, %107, %108, %109, %110, %111, "
        "%112, %113, %114, %115, %116, %117, %118, %119, %120, %121, %122, %123, %124, %125, %126, %127}, "
        "%128, %129, p, 1, 1, 0, 0;\n"
        "}\n"
        : ACC8(d, 0), ACC8(d, 8), ACC8(d, 16), ACC8(d, 24), ACC8(d, 32), ACC8(d, 40), ACC8(d, 48), ACC8(d, 56),
          ACC8(d, 64), ACC8(d, 72), ACC8(d, 80), ACC8(d, 88), ACC8(d, 96), ACC8(d, 104), ACC8(d, 112), ACC8(d, 120)
        : "l"(da), "l"(db), "r"(scale_d));
}

__device__ __forceinline__ void mma_bf16_16816(float (&c)[4], uint32_t a0, uint32_t a1, uint32_t a2, uint32_t a3,
                                               uint32_t b0, uint32_t b1) {
    asm volatile(
        "mma.sync.aligned.m16n8k16.row.col.f32.bf16.bf16.f32 {%0,%1,%2,%3}, {%4,%5,%6,%7}, {%8,%9}, {%0,%1,%2,%3};"
        : "+f"(c[0]), "+f"(c[1]), "+f"(c[2]), "+f"(c[3])
        : "r"(a0), "r"(a1), "r"(a2), "r"(a3), "r"(b0), "r"(b1));
}

__device__ __forceinline__ uint32_t lds32(uint32_t addr) {
    uint32_t v;
    asm volatile("ld.shared.b32 %0, [%1];" : "=r"(v) : "r"(addr));
    return v;
}
__device__ __forceinline__ uint32_t pack_bf16(float lo, float hi) {
    __nv_bfloat162 t = __floats2bfloat162_rn(lo, hi);
    return *reinterpret_cast<uint32_t*>(&t);
}
__device__ __forceinline__ float bf_lo(uint32_t v) { return __uint_as_float(v << 16); }
__device__ __forceinline__ float bf_hi(uint32_t v) { return __uint_as_float(v & 0xffff0000u); }
__device__ __forceinline__ __nv_bfloat162 u2b(uint32_t v) { return *reinterpret_cast<__nv_bfloat162*>(&v); }
__device__ __forceinline__ uint32_t b2u(__nv_bfloat162 v) { return *reinterpret_cast<uint32_t*>(&v); }
__device__ __forceinline__ float rbf(float x) { return __bfloat162float(__float2bfloat16_rn(x)); }

__device__ __forceinline__ void named_bar_sync(int id, int n) {
    asm volatile("bar.sync %0, %1;" ::"r"(id), "r"(n) : "memory");
}

constexpr int BM = 128, BN = 256, BK = 64, STAGES = 4;
constexpr int A_BYTES = BM * BK * 2;
constexpr int B_BYTES = BN * BK * 2;
constexpr int STAGE_BYTES = A_BYTES + B_BYTES;
constexpr int SMEM_BYTES = STAGES * STAGE_BYTES + 34688 + 1024;
constexpr int NTHREADS = 384;

constexpr int STG_PITCH = 528;
constexpr int STG_WG_BYTES = 64 * STG_PITCH;

constexpr int KV_PITCH = 112 + 2048 + 8;
constexpr int KV_BYTES = 8 * KV_PITCH * 2;
constexpr int REV_PITCH = 2096;
constexpr int REV_BYTES = 8 * 2 * REV_PITCH * 2;
constexpr int YS_BYTES = 2048 * 8 * 2;
constexpr int CONV_KV_OFF = STAGES * STAGE_BYTES;
constexpr int CONV_REV_OFF = 2 * STAGE_BYTES;
constexpr int STG1_OFF = 2 * STAGE_BYTES;
constexpr int CONV_YS_OFF = CONV_REV_OFF + REV_BYTES;
static_assert(CONV_REV_OFF + REV_BYTES <= STAGES * STAGE_BYTES && STG1_OFF + 2 * STG_WG_BYTES <= STAGES * STAGE_BYTES && KV_BYTES <= 34688, "conv smem");
constexpr int REV_Y0 = 2054;

struct Params {
    const __nv_bfloat16 *q, *k, *v, *shift_k, *ssm_k, *ssm_D;
    __nv_bfloat16* out;
};

struct PipeState {
    int stage;
    uint32_t phase;
    __device__ __forceinline__ void advance() {
        if (++stage == STAGES) { stage = 0; phase ^= 1; }
    }
};

template <bool B_MC>
__device__ __forceinline__ void gemm_produce(PipeState& ps, uint32_t sbase, uint32_t full0, uint32_t empty0,
                                             const CUtensorMap* mA, const CUtensorMap* mB, int arow, int brow,
                                             int ahalf, int bhalf, uint16_t maskA, uint16_t maskB, int k0, int nk) {
#pragma unroll 1
    for (int it = k0; it < nk; ++it) {
        mbar_wait(empty0 + 8 * ps.stage, ps.phase ^ 1);
        uint32_t fb = full0 + 8 * ps.stage;
        mbar_expect_tx(fb, STAGE_BYTES);
        uint32_t sa = sbase + ps.stage * STAGE_BYTES;
        tma_load_2d(sa, mA, fb, it * BK, arow);
        tma_load_2d(sa + A_BYTES / 2, mA, fb, it * BK, arow + BM / 2);
        if (B_MC) {
            tma_load_2d_mc(sa + A_BYTES + bhalf * (B_BYTES / 2), mB, fb, it * BK, brow + bhalf * (BN / 2), maskB);
        } else {
            tma_load_2d(sa + A_BYTES, mB, fb, it * BK, brow);
            tma_load_2d(sa + A_BYTES + B_BYTES / 2, mB, fb, it * BK, brow + BN / 2);
        }
        ps.advance();
    }
}

__device__ __forceinline__ void release_stage(uint32_t empty0, uint32_t emptyA, uint32_t emptyB, int stage) {
    if ((threadIdx.x & 31) == 0) {
        mbar_arrive(empty0 + 8 * stage);
        mbar_arrive_cluster(emptyB + 8 * stage);
    }
}

__device__ __forceinline__ void gemm_consume(PipeState& ps, float (&acc)[128], uint32_t sbase, uint32_t full0,
                                             uint32_t empty0, uint32_t emptyA, uint32_t emptyB, int wg, int nk,
                                             int n_hold) {
    int prev_stage = -1;
#pragma unroll 1
    for (int it = 0; it < nk; ++it) {
        mbar_wait(full0 + 8 * ps.stage, ps.phase);
        uint32_t sa = sbase + ps.stage * STAGE_BYTES + wg * (64 * 128);
        uint32_t sb = sbase + ps.stage * STAGE_BYTES + A_BYTES;
        uint64_t da = make_desc_sw128(sa);
        uint64_t db = make_desc_sw128(sb);
        wgmma_fence();
#pragma unroll
        for (int kk = 0; kk < 4; ++kk) {
            wgmma_m64n256k16(acc, da + (uint64_t)(kk * 2), db + (uint64_t)(kk * 2), (it > 0 || kk > 0) ? 1 : 0);
        }
        wgmma_commit();
        if (prev_stage >= 0) {
            wgmma_wait<1>();
            if (it - 1 < nk - n_hold) release_stage(empty0, emptyA, emptyB, prev_stage);
        }
        prev_stage = ps.stage;
        ps.advance();
    }
    wgmma_wait<0>();
    if (n_hold == 0) release_stage(empty0, emptyA, emptyB, prev_stage);
}

__device__ __forceinline__ void store_tile_bf16(const uint32_t (&pk)[64], uint8_t* stg, __nv_bfloat16* gdst, int ld,
                                                int wg_tid, int bar_id) {
    const int warp = wg_tid >> 5, lane = wg_tid & 31;
    const int r0 = warp * 16 + (lane >> 2);
    const int c0 = (lane & 3) * 2;
#pragma unroll
    for (int j = 0; j < 32; ++j) {
        *reinterpret_cast<uint32_t*>(stg + r0 * STG_PITCH + (j * 8 + c0) * 2) = pk[2 * j];
        *reinterpret_cast<uint32_t*>(stg + (r0 + 8) * STG_PITCH + (j * 8 + c0) * 2) = pk[2 * j + 1];
    }
    named_bar_sync(bar_id, 128);
#pragma unroll
    for (int p = 0; p < 16; ++p) {
        int r = p * 4 + (wg_tid >> 5);
        int cb = (wg_tid & 31) * 16;
        uint4 val = *reinterpret_cast<const uint4*>(stg + r * STG_PITCH + cb);
        *reinterpret_cast<uint4*>(reinterpret_cast<uint8_t*>(gdst + (size_t)r * ld) + cb) = val;
    }
}

__device__ __forceinline__ void counter_wait(unsigned int* ready, unsigned int* passed, unsigned int n_ready,
                                             unsigned int n_wait) {
    unsigned int v;
    long long spins = 0;
    do {
        asm volatile("ld.acquire.gpu.global.u32 %0, [%1];" : "=r"(v) : "l"(ready) : "memory");
    } while (v < n_ready && ++spins < (1ll << 26));
    unsigned int old = atomicAdd(passed, 1u);
    if (old == n_wait - 1) {
        *passed = 0;
        *ready = 0;
        __threadfence();
    }
}

__device__ __forceinline__ void kv_prepass(const Params& p, int s0, int ctid) {
    const int c0 = ctid * 4;
    uint2 kr[19], vr[16];
#pragma unroll
    for (int j = 0; j < 19; ++j) {
        int s = s0 - 3 + j;
        if (s >= 0) kr[j] = __ldg(reinterpret_cast<const uint2*>(p.k + (size_t)s * D_DIM + c0));
        else kr[j] = make_uint2(0, 0);
    }
#pragma unroll
    for (int j = 0; j < 16; ++j) vr[j] = __ldg(reinterpret_cast<const uint2*>(p.v + (size_t)(s0 + j) * D_DIM + c0));
    uint4 w0 = __ldg(reinterpret_cast<const uint4*>(p.shift_k + (size_t)c0 * 4));
    uint4 w1 = __ldg(reinterpret_cast<const uint4*>(p.shift_k + (size_t)c0 * 4 + 8));
    uint32_t wt[2][4];
    wt[0][0] = __byte_perm(w0.x, w0.z, 0x5410); wt[0][1] = __byte_perm(w0.x, w0.z, 0x7632);
    wt[0][2] = __byte_perm(w0.y, w0.w, 0x5410); wt[0][3] = __byte_perm(w0.y, w0.w, 0x7632);
    wt[1][0] = __byte_perm(w1.x, w1.z, 0x5410); wt[1][1] = __byte_perm(w1.x, w1.z, 0x7632);
    wt[1][2] = __byte_perm(w1.y, w1.w, 0x5410); wt[1][3] = __byte_perm(w1.y, w1.w, 0x7632);
#pragma unroll
    for (int pr = 0; pr < 2; ++pr) {
        uint32_t r[16];
#pragma unroll
        for (int j = 0; j < 16; ++j) {
            __nv_bfloat162 k0 = u2b(pr ? kr[j].y : kr[j].x), k1 = u2b(pr ? kr[j + 1].y : kr[j + 1].x);
            __nv_bfloat162 k2 = u2b(pr ? kr[j + 2].y : kr[j + 2].x), k3 = u2b(pr ? kr[j + 3].y : kr[j + 3].x);
            __nv_bfloat162 acc = __hmul2(k0, u2b(wt[pr][3]));
            acc = __hadd2(acc, __hmul2(k1, u2b(wt[pr][2])));
            acc = __hadd2(acc, __hmul2(k2, u2b(wt[pr][1])));
            acc = __hadd2(acc, __hmul2(k3, u2b(wt[pr][0])));
            acc = __hmul2(acc, u2b(pr ? vr[j].y : vr[j].x));
            r[j] = b2u(acc);
        }
        uint32_t lo[8], hi[8];
#pragma unroll
        for (int j = 0; j < 8; ++j) {
            lo[j] = __byte_perm(r[2 * j], r[2 * j + 1], 0x5410);
            hi[j] = __byte_perm(r[2 * j], r[2 * j + 1], 0x7632);
        }
        uint4* d0 = reinterpret_cast<uint4*>(g_kvT + (size_t)(c0 + 2 * pr) * S_LEN + s0);
        uint4* d1 = reinterpret_cast<uint4*>(g_kvT + (size_t)(c0 + 2 * pr + 1) * S_LEN + s0);
        d0[0] = make_uint4(lo[0], lo[1], lo[2], lo[3]);
        d0[1] = make_uint4(lo[4], lo[5], lo[6], lo[7]);
        d1[0] = make_uint4(hi[0], hi[1], hi[2], hi[3]);
        d1[1] = make_uint4(hi[4], hi[5], hi[6], hi[7]);
    }
}

__device__ __forceinline__ void out_postpass(const Params& p, int s0, int ctid) {
    const int c0 = ctid * 4;
    uint2 qr[16];
#pragma unroll
    for (int j = 0; j < 16; ++j) qr[j] = __ldg(reinterpret_cast<const uint2*>(p.q + (size_t)(s0 + j) * D_DIM + c0));
    uint4 yy[4][2];
#pragma unroll
    for (int c = 0; c < 4; ++c) {
        const uint4* src = reinterpret_cast<const uint4*>(g_yT + (size_t)(c0 + c) * S_LEN + s0);
        yy[c][0] = __ldcg(src);
        yy[c][1] = __ldcg(src + 1);
    }
#pragma unroll
    for (int j = 0; j < 16; j += 2) {
        uint32_t y0 = reinterpret_cast<const uint32_t*>(&yy[0][0])[j >> 1], y1 = reinterpret_cast<const uint32_t*>(&yy[1][0])[j >> 1];
        uint32_t y2 = reinterpret_cast<const uint32_t*>(&yy[2][0])[j >> 1], y3 = reinterpret_cast<const uint32_t*>(&yy[3][0])[j >> 1];
        uint2 o;
        o.x = b2u(__hmul2(u2b(qr[j].x), u2b(__byte_perm(y0, y1, 0x5410))));
        o.y = b2u(__hmul2(u2b(qr[j].y), u2b(__byte_perm(y2, y3, 0x5410))));
        *reinterpret_cast<uint2*>(p.out + (size_t)(s0 + j) * 2048 + 1024 + c0) = o;
        o.x = b2u(__hmul2(u2b(qr[j + 1].x), u2b(__byte_perm(y0, y1, 0x7632))));
        o.y = b2u(__hmul2(u2b(qr[j + 1].y), u2b(__byte_perm(y2, y3, 0x7632))));
        *reinterpret_cast<uint2*>(p.out + (size_t)(s0 + j + 1) * 2048 + 1024 + c0) = o;
    }
}

__device__ __forceinline__ void conv_phase(const Params& p, uint8_t* smem, int ch0, int ctid, const uint4 (&hv)[8], const uint4 (&t)[8]) {
    const int warp = ctid >> 5, lane = ctid & 31;
    __nv_bfloat16* kvs = reinterpret_cast<__nv_bfloat16*>(smem + CONV_KV_OFF) + (size_t)warp * KV_PITCH;
    __nv_bfloat16* rev = reinterpret_cast<__nv_bfloat16*>(smem + CONV_REV_OFF);

    {
        __nv_bfloat16* r0 = rev + (size_t)(warp * 2) * REV_PITCH;
        __nv_bfloat16* r1 = r0 + REV_PITCH;
        const unsigned short* hraw = reinterpret_cast<const unsigned short*>(p.ssm_k + (size_t)(ch0 + warp) * S_LEN);
#pragma unroll
        for (int it = 0; it < 8; ++it) {
            int idx = 8 * (lane + 32 * it);
            uint32_t prev = (idx > 0) ? (uint32_t)__ldg(hraw + idx - 1) : 0u;
            uint4 h4 = hv[it];
            uint4 o1, o0;
            o1.x = __byte_perm(h4.w, 0, 0x1032); o1.y = __byte_perm(h4.z, 0, 0x1032);
            o1.z = __byte_perm(h4.y, 0, 0x1032); o1.w = __byte_perm(h4.x, 0, 0x1032);
            *reinterpret_cast<uint4*>(r1 + (REV_Y0 - 6 - idx)) = o1;
            o0.x = __byte_perm(h4.w, h4.z, 0x7610);
            o0.y = __byte_perm(h4.z, h4.y, 0x7610);
            o0.z = __byte_perm(h4.y, h4.x, 0x7610);
            o0.w = __byte_perm(h4.x, prev, 0x5410);
            *reinterpret_cast<uint4*>(r0 + (REV_Y0 - 6 - idx)) = o0;
        }
        if (lane == 31) r0[REV_Y0 - 2047] = reinterpret_cast<const __nv_bfloat16*>(&hv[7])[7];
        if (lane < 24) {
            int idx = -1 - lane;
            r0[REV_Y0 - idx] = __float2bfloat16_rn(0.f);
            r1[REV_Y0 + 1 - idx] = __float2bfloat16_rn(0.f);
        }
    }
    {
#pragma unroll
        for (int it = 0; it < 8; ++it) *reinterpret_cast<uint4*>(kvs + 112 + 8 * (lane + 32 * it)) = t[it];
        if (lane < 14) *reinterpret_cast<uint4*>(kvs + lane * 8) = make_uint4(0, 0, 0, 0);
    }
    __syncwarp();
    TSTAMP(6);
    float acc[16][4];
#pragma unroll
    for (int i = 0; i < 16; ++i) { acc[i][0] = acc[i][1] = acc[i][2] = acc[i][3] = 0.f; }
    const int g = lane >> 2, c2 = (lane & 3) * 2;
    const uint32_t rev_base = smem_u32(rev + (size_t)(warp * 2 + (g & 1)) * REV_PITCH) +
                              2u * (uint32_t)(REV_Y0 + (g & 1) - g + c2);
    const uint32_t kv_base = smem_u32(kvs + 112) + 2u * (uint32_t)(16 * g + c2);
#pragma unroll 1
    for (int a = 0; a < 8; ++a) {
        uint32_t f[16][3];
#pragma unroll
        for (int q = 0; q < 16; ++q) {
            int delta = 16 * a + 128 * q;
            f[q][0] = lds32(rev_base - 2u * (uint32_t)(delta - 8));
            f[q][1] = lds32(rev_base - 2u * (uint32_t)(delta));
            f[q][2] = lds32(rev_base - 2u * (uint32_t)(delta + 8));
        }
        const uint32_t kva = kv_base - 32u * (uint32_t)a;
#pragma unroll
        for (int G = 0; G < 16; ++G) {
            uint32_t b0 = lds32(kva + 256u * G);
            uint32_t b1 = lds32(kva + 256u * G + 16u);
#pragma unroll
            for (int q = 0; q < 16 - G; ++q) {
                mma_bf16_16816(acc[G + q], f[q][1], f[q][2], f[q][0], f[q][1], b0, b1);
            }
        }
    }
    TSTAMP(7);
    __syncwarp();
    {
        const float Dv = __bfloat162float(p.ssm_D[ch0 + warp]);
        __nv_bfloat16* kvc = kvs + 112;
#pragma unroll
        for (int I = 0; I < 16; ++I) {
#pragma unroll
            for (int e = 0; e < 4; ++e) {
                int s = 16 * (8 * I + c2 + (e & 1)) + g + 8 * (e >> 1);
                float kvv = __bfloat162float(kvc[s]);
                float y = rbf(acc[I][e]) + rbf(kvv * Dv);
                kvc[s] = __float2bfloat16_rn(y);
            }
        }
        __syncwarp();
        uint4* dst = reinterpret_cast<uint4*>(g_yT + (size_t)(ch0 + warp) * S_LEN);
#pragma unroll
        for (int it = 0; it < 8; ++it) dst[lane + 32 * it] = *reinterpret_cast<const uint4*>(kvc + 8 * (lane + 32 * it));
    }
}

__global__ void __cluster_dims__(2, 1, 1) __launch_bounds__(NTHREADS, 1)
fused_kernel(const __grid_constant__ CUtensorMap mWre, const __grid_constant__ CUtensorMap mWim,
             const __grid_constant__ CUtensorMap mX, const __grid_constant__ CUtensorMap mAB,
             const __grid_constant__ CUtensorMap mCr, const __grid_constant__ CUtensorMap mCi,
             const Params p) {
    extern __shared__ uint8_t smem_raw[];
    __shared__ __align__(8) uint64_t bars[2 * STAGES];
    uint8_t* smem = smem_raw + ((1024u - (smem_u32(smem_raw) & 1023u)) & 1023u);
    const uint32_t sbase = smem_u32(smem);
    const uint32_t full0 = smem_u32(&bars[0]);
    const uint32_t empty0 = smem_u32(&bars[STAGES]);
    const int tid = threadIdx.x;
    const int wgid = tid >> 7;
    const int bid = blockIdx.x;

    if (tid == 0) {
        for (int i = 0; i < STAGES; ++i) {
            mbar_init(full0 + 8 * i, 1);
            mbar_init(empty0 + 8 * i, 16);
        }
        asm volatile("fence.mbarrier_init.release.cluster;" ::: "memory");
    }
    __syncthreads();
    cluster_sync_all();

    const int rank = bid & 1, pair = bid >> 1;
    const int g1_m = 2 * (pair >> 3) + rank, g1_n = pair & 7;
    const int part = rank;
    const int g2_m = pair >> 2, g2_n = pair & 3;
    const int grp = part * 4 + g2_n;

    if (wgid == 0) {
        if (tid == 0) {
            PipeState ps{0, 0};
            const CUtensorMap* mW = (g1_m < 8) ? &mWre : &mWim;
            gemm_produce<true>(ps, sbase, full0, empty0, mW, &mX, (g1_m & 7) * BM, g1_n * BN, 0, rank, 0, 3, 0, D_DIM / BK);
        }
        if (tid >= 32) {
#pragma unroll 1
            for (int t = tid - 32; t < 256; t += 96) { kv_prepass(p, bid * 16, t); TSTAMP2(8 + t / 96); }
            named_bar_sync(5, 96);
            TSTAMP2(11);
            if (tid == 32) asm volatile("red.release.gpu.global.add.u32 [%0], 1;" ::"l"(&g_sync[0]) : "memory");
            if (tid < 64) {
                __syncwarp();
                named_bar_sync(6, 288);
                if (tid == 32) {
                    asm volatile("fence.proxy.async;" ::: "memory");
                    asm volatile("red.release.gpu.global.add.u32 [%0], 1;" ::"l"(&g_ready[g1_m >> 1]) : "memory");
                }
             }
        }
        const CUtensorMap* mC = part ? &mCi : &mCr;
        PipeState ps2{0, 0};
        if (tid == 0) {
            counter_wait(&g_ready[grp], &g_passed[grp], 16u, 16u);
            asm volatile("fence.proxy.async;" ::: "memory");
            gemm_produce<false>(ps2, sbase, full0, empty0, mC, &mAB, g2_m * BM, grp * BN, 0, 0, 0, 0, 0, 2);
#pragma unroll 1
            for (int it = g2_n * 8; it < g2_n * 8 + 8; ++it) {
                asm volatile("cp.async.bulk.prefetch.tensor.2d.L2.global [%0, {%1, %2}];" ::"l"((uint64_t)mC),
                             "r"(it * BK), "r"(g2_m * BM) : "memory");
                asm volatile("cp.async.bulk.prefetch.tensor.2d.L2.global [%0, {%1, %2}];" ::"l"((uint64_t)mC),
                             "r"(it * BK), "r"(g2_m * BM + 64) : "memory");
            }
        }
        if (tid == 0) {
            gemm_produce<false>(ps2, sbase, full0, empty0, mC, &mAB, g2_m * BM, grp * BN, 0, 0, 0, 0, 2, S_LEN / BK);
        }
        if (tid >= 32) {
            if (tid == 32) counter_wait(&g_sync[2], &g_sync[3], 128u, 128u);
            named_bar_sync(5, 96);
#pragma unroll 1
            for (int t = tid - 32; t < 256; t += 96) out_postpass(p, bid * 16, t);
        }
        __syncwarp();
        asm volatile("barrier.cluster.arrive.release.aligned;\n barrier.cluster.wait.acquire.aligned;" ::: "memory");
        asm volatile("barrier.cluster.arrive.release.aligned;\n barrier.cluster.wait.acquire.aligned;" ::: "memory");
    } else {
        const int wg = wgid - 1;
        const int ctid = tid - 128;
        const int wtid = tid & 127;
        PipeState ps{0, 0};
        float acc[128];
        const uint32_t emptyA = 0, emptyB = mapa_u32(empty0, rank ^ 1);
        TSTAMP(0);
        gemm_consume(ps, acc, sbase, full0, empty0, emptyA, emptyB, wg, D_DIM / BK, 2);
        named_bar_sync(1, 256);
        TSTAMP(1);
        uint4 hv[8], kvr[8];
        {
            uint32_t pk[64];
#pragma unroll
            for (int i = 0; i < 64; ++i) pk[i] = pack_bf16(acc[2 * i], acc[2 * i + 1]);
            if (ctid == 0) counter_wait(&g_sync[0], &g_sync[1], 128u, 128u);
            named_bar_sync(1, 256);
            {
                const int cw = ctid >> 5, cl = ctid & 31;
                const uint4* hs = reinterpret_cast<const uint4*>(p.ssm_k + (size_t)(bid * 8 + cw) * S_LEN);
                const uint4* ks = reinterpret_cast<const uint4*>(g_kvT + (size_t)(bid * 8 + cw) * S_LEN);
#pragma unroll
                for (int it = 0; it < 8; ++it) { hv[it] = __ldg(hs + cl + 32 * it); kvr[it] = __ldcg(ks + cl + 32 * it); }
            }
            __nv_bfloat16* dst = g_abT + (size_t)(g1_m * BM + wg * 64) * 2048 + g1_n * BN;
            store_tile_bf16(pk, smem + STG1_OFF + wg * STG_WG_BYTES, dst, 2048, wtid, 3 + wg);
        }
        asm volatile("bar.arrive 6, 288;" ::: "memory");
        TSTAMP(2);
        named_bar_sync(1, 256);
        conv_phase(p, smem, bid * 8, ctid, hv, kvr);
        asm volatile("fence.proxy.async.shared::cta;" ::: "memory");
        __syncwarp();
        release_stage(empty0, emptyA, emptyB, 2);
        release_stage(empty0, emptyA, emptyB, 3);
        named_bar_sync(1, 256);
        if (ctid == 0) asm volatile("red.release.gpu.global.add.u32 [%0], 1;" ::"l"(&g_sync[2]) : "memory");
        TSTAMP(3);
#pragma unroll
        for (int i = 0; i < 128; ++i) acc[i] = 0.f;
        gemm_consume(ps, acc, sbase, full0, empty0, emptyA, emptyB, wg, S_LEN / BK, 0);
        named_bar_sync(1, 256);
        TSTAMP(4);
        asm volatile("barrier.cluster.arrive.release.aligned;\n barrier.cluster.wait.acquire.aligned;" ::: "memory");
        uint32_t pk[64];
#pragma unroll
        for (int i = 0; i < 64; ++i) pk[i] = pack_bf16(acc[2 * i], acc[2 * i + 1]);
        const uint32_t xbuf = sbase + 2 * STG_WG_BYTES + 1024;
        const bool sender = (wg != part);
        if (sender) {
            uint32_t remote;
            remote = mapa_u32(xbuf, rank ^ 1);
#pragma unroll
            for (int i = 0; i < 64; ++i) {
                asm volatile("st.shared::cluster.b32 [%0], %1;" ::"r"(remote + (uint32_t)(i * 512 + wtid * 4)), "r"(pk[i]) : "memory");
            }
        }
        asm volatile("barrier.cluster.arrive.release.aligned;\n barrier.cluster.wait.acquire.aligned;" ::: "memory");
        if (!sender) {
#pragma unroll
            for (int i = 0; i < 64; ++i) {
                uint32_t o = lds32(xbuf + (uint32_t)(i * 512 + wtid * 4));
                uint32_t re = part ? o : pk[i];
                uint32_t im = part ? pk[i] : o;
                pk[i] = pack_bf16(bf_lo(re) - bf_lo(im), bf_hi(re) - bf_hi(im));
            }
            __nv_bfloat16* dst = p.out + (size_t)(g2_m * BM + wg * 64) * 2048 + g2_n * BN;
            store_tile_bf16(pk, smem + wg * STG_WG_BYTES, dst, 2048, wtid, 3 + wg);
        }
        TSTAMP(5);
    }
}

typedef CUresult (*PFN_encodeTiled)(CUtensorMap*, CUtensorMapDataType, cuuint32_t, void*, const cuuint64_t*,
                                    const cuuint64_t*, const cuuint32_t*, const cuuint32_t*, CUtensorMapInterleave,
                                    CUtensorMapSwizzle, CUtensorMapL2promotion, CUtensorMapFloatOOBfill);

static void make_map(PFN_encodeTiled enc, CUtensorMap* m, const void* ptr, int rows, int cols, int box_rows) {
    cuuint64_t gdim[2] = {(cuuint64_t)cols, (cuuint64_t)rows};
    cuuint64_t gstr[1] = {(cuuint64_t)cols * 2};
    cuuint32_t box[2] = {64, (cuuint32_t)box_rows};
    cuuint32_t estr[2] = {1, 1};
    enc(m, CU_TENSOR_MAP_DATA_TYPE_BFLOAT16, 2, const_cast<void*>(ptr), gdim, gstr, box, estr,
        CU_TENSOR_MAP_INTERLEAVE_NONE, CU_TENSOR_MAP_SWIZZLE_128B, CU_TENSOR_MAP_L2_PROMOTION_L2_256B,
        CU_TENSOR_MAP_FLOAT_OOB_FILL_NONE);
}

extern "C" void kernel_launch(void* const* d_in, const int* in_sizes, int n_in, void* d_out, int out_size) {
    static PFN_encodeTiled enc = nullptr;
    static bool attr_set = false;
    if (!enc) {
        void* fn = nullptr;
        cudaDriverEntryPointQueryResult qres;
        cudaGetDriverEntryPoint("cuTensorMapEncodeTiled", &fn, cudaEnableDefault, &qres);
        enc = (PFN_encodeTiled)fn;
    }
    if (!attr_set) {
        cudaFuncSetAttribute(fused_kernel, cudaFuncAttributeMaxDynamicSharedMemorySize, SMEM_BYTES);
        attr_set = true;
    }
    void* abT = nullptr;
    cudaGetSymbolAddress(&abT, g_abT);

    CUtensorMap mWre, mWim, mX, mAB, mCr, mCi;
    make_map(enc, &mX, d_in[0], 2048, 1024, BN / 2);
    make_map(enc, &mCr, d_in[1], 2048, 2048, BM / 2);
    make_map(enc, &mCi, d_in[2], 2048, 2048, BM / 2);
    make_map(enc, &mWre, d_in[3], 1024, 1024, BM / 2);
    make_map(enc, &mWim, d_in[4], 1024, 1024, BM / 2);
    make_map(enc, &mAB, abT, 2048, 2048, BN / 2);

    Params p;
    p.q = (const __nv_bfloat16*)d_in[5];
    p.k = (const __nv_bfloat16*)d_in[6];
    p.v = (const __nv_bfloat16*)d_in[7];
    p.shift_k = (const __nv_bfloat16*)d_in[8];
    p.ssm_k = (const __nv_bfloat16*)d_in[9];
    p.ssm_D = (const __nv_bfloat16*)d_in[10];
    p.out = (__nv_bfloat16*)d_out;

    fused_kernel<<<128, NTHREADS, SMEM_BYTES>>>(mWre, mWim, mX, mAB, mCr, mCi, p);
}
```
